```python
import torch

def _softmax(x, axis=-1):
    return torch.softmax(x, dim=axis)
def _gelu(x):
    return torch.nn.functional.gelu(x, approximate="tanh")
def _silu(x):
    return torch.nn.functional.silu(x)
def _sigmoid(x):
    return torch.sigmoid(x)
def _layernorm(x, axis=-1, eps=1e-5):
    m = x.mean(dim=axis, keepdim=True)
    v = x.var(dim=axis, keepdim=True, unbiased=False)
    return (x - m) / torch.sqrt(v + eps)
def _scatter_add(tgt, idx, src, axis=0):
    return tgt.clone().index_add_(axis, idx, src)
def _segment_sum(src, seg, n):
    out = torch.zeros((n,) + src.shape[1:], dtype=src.dtype)
    return out.index_add_(0, seg, src)
def _pad(x, pw):
    flat = tuple(v for pair in reversed(pw) for v in pair)
    return torch.nn.functional.pad(x, flat)

kernel_name = 'parallel_sum__ssm_conv_s4__dense_activation_relu__prompt'

def setup_inputs():

    _w = (lambda a: (lambda t: t.to(torch.bfloat16) if t.is_floating_point() else t)(torch.as_tensor(a)))
    def _A_setup():
        B, L, D, N = 1, 2048, 512, 128
        A_re = -(lambda _x: torch.exp(torch.as_tensor(_x)))((lambda *s: torch.randn(*s, dtype=torch.bfloat16) * 3.2)(D, N))
        A_im = torch.pi * (lambda *s: torch.randn(*s, dtype=torch.bfloat16) * 0.1)(D, N)
        B_re = (lambda *s: torch.randn(*s, dtype=torch.bfloat16) * 0.4)(D, N)
        B_im = (lambda *s: torch.randn(*s, dtype=torch.bfloat16) * 0.4)(D, N)
        C_re = (lambda *s: torch.randn(*s, dtype=torch.bfloat16) * 0.4)(D, N)
        C_im = (lambda *s: torch.randn(*s, dtype=torch.bfloat16) * 0.4)(D, N)
        log_dt = (lambda *s: torch.randn(*s, dtype=torch.bfloat16) * 0.1)(D) * 0.5 - 4.0
        Dskip = (lambda *s: torch.randn(*s, dtype=torch.bfloat16) * 0.2)(D)
        return {
            "u": _w((lambda *s: torch.randn(*s, dtype=torch.bfloat16) * 0.05)(B, L, D)),
            "A_re": _w(A_re),
            "A_im": _w(A_im),
            "B_re": _w(B_re),
            "B_im": _w(B_im),
            "C_re": _w(C_re),
            "C_im": _w(C_im),
            "log_dt": _w(log_dt),
            "Dskip": _w(Dskip),
        }
    _A_in = _A_setup()

    def _B_setup():
        B, S, D, Dff = 1, 2048, 512, 1376
        return {
            "x": _w((lambda *s: torch.randn(*s, dtype=torch.bfloat16) * 0.05)(B, S, D)),
            "w1": _w((lambda *s: torch.randn(*s, dtype=torch.bfloat16) * 0.05)(D, Dff)),
            "w2": _w((lambda *s: torch.randn(*s, dtype=torch.bfloat16) * 0.05)(Dff, D)),
        }
    _B_in = _B_setup()

    return {
        "A_u": _A_in["u"],
        "A_A_re": _A_in["A_re"],
        "A_A_im": _A_in["A_im"],
        "A_B_re": _A_in["B_re"],
        "A_B_im": _A_in["B_im"],
        "A_C_re": _A_in["C_re"],
        "A_C_im": _A_in["C_im"],
        "A_log_dt": _A_in["log_dt"],
        "A_Dskip": _A_in["Dskip"],
        "B_x": _B_in["x"],
        "B_w1": _B_in["w1"],
        "B_w2": _B_in["w2"],
    }

def reference(A_u, A_A_re, A_A_im, A_B_re, A_B_im, A_C_re, A_C_im, A_log_dt, A_Dskip, B_x, B_w1, B_w2):
    def _A_ref(u, A_re, A_im, B_re, B_im, C_re, C_im, log_dt, Dskip):
        Bsz, L, D = u.shape
        dt = torch.exp(log_dt)[:, None]
        A = A_re + 1j * A_im
        Bc = B_re + 1j * B_im
        Cc = C_re + 1j * C_im
        logdA = dt * A
        dB = dt * Bc
        l = (lambda x, dt: x.to(dt))(torch.arange(L), A_re.dtype)
        P = torch.exp(logdA[:, :, None] * l[None, None, :])
        K = torch.einsum("dn,dnl,dn->dl", Cc, P, dB).real
        L2 = 2 * L
        Kp = _pad(K, ((0, 0), (0, L)))
        up = (lambda x, *d: x.permute(*d))(u, 0, 2, 1)
        up = _pad(up, ((0, 0), (0, 0), (0, L)))
        Kf = (lambda x, axes=(-2,-1): torch.fft.rfft2(x.float(), dim=axes))(Kp[:, None, :], axes=(-2, -1))
        Uf = (lambda x, axes=(-2,-1): torch.fft.rfft2(x.float(), dim=axes))(up[:, :, None, :], axes=(-2, -1))
        Yf = Uf * Kf[None, :, :, :]
        y = (lambda x, s, axes=(-2,-1): torch.fft.irfft2(x, s=s, dim=axes).to(torch.bfloat16))(Yf, (1, L2), axes=(-2, -1))[:, :, 0, :L]
        y = (lambda x, *d: x.permute(*d))(y, 0, 2, 1) + u * Dskip[None, None, :]
        return y

    def _B_ref(x, w1, w2):
        h = torch.einsum("bsd,df->bsf", x, w1)
        zero = torch.zeros_like(h)
        h = torch.maximum(h, zero)
        return torch.einsum("bsf,fd->bsd", h, w2)

    x = A_u
    xn = _layernorm(x, axis=-1)
    return x + _A_ref(xn, A_A_re, A_A_im, A_B_re, A_B_im, A_C_re, A_C_im, A_log_dt, A_Dskip) + _B_ref(xn, B_w1, B_w2)
```

```cpp
#include <cuda_runtime.h>
#include <cuda_bf16.h>
#include <cuda.h>
#include <stdint.h>

typedef __nv_bfloat16 bf16;

__device__ __align__(1024) bf16 g_xnP[512 * 2048];
__device__ __align__(1024) bf16 g_h[2048 * 1376];
__device__ __align__(1024) bf16 g_yT[512 * 2048];
__device__ __align__(128) float2 g_stat[2048];
__device__ __align__(128) float g_colsum[1408];
__device__ __align__(128) unsigned g_cnt[32 * 32];
#define TS(k)
#define TS1(k)
#define CNT_PREP 0
#define CNT_DONE 32
#define CNT_H(i) (64 + 32 * (i))
#define CNT_Y(j) (64 + 32 * 16 + 32 * (j))

constexpr int SM_HST = 118784;
constexpr int SM_XT = 147456;
constexpr int SM_U = 163840;
constexpr int U_CH = 5248, U_PL = 656;
constexpr int SM_KT = 184832;
constexpr int KT_CH = 3712, KT_Z5 = 2560, KT_Z3 = 2944, KT_Z4 = 3328;
constexpr int SM_WORK = 199680;
constexpr int WK_SZ = 15360;
constexpr int WK_S5 = 0, WK_S3 = 3456, WK_S9 = 6656, WK_S7 = 8832, WK_F = 11008;
constexpr int WK_BT = 0, WK_PRM = 8704, WK_KV = 10752;
constexpr int SM_STAT = 230400;
constexpr int SM_COLS = 231424;
constexpr int SM_BAR = 232128;
constexpr int SM_TOTAL = 232384;
constexpr int B_F1 = 0, B_E1 = 4, B_F2 = 8, B_E2 = 14, B_MISC = 20, B_U = 21, B_X = 22, B_Y = 23;

__device__ __forceinline__ uint32_t smem_u32(const void* p) { return (uint32_t)__cvta_generic_to_shared(p); }
__device__ __forceinline__ void mbar_init(uint32_t bar, uint32_t cnt) { asm volatile("mbarrier.init.shared::cta.b64 [%0], %1;" ::"r"(bar), "r"(cnt) : "memory"); }
__device__ __forceinline__ void mbar_expect(uint32_t bar, uint32_t bytes) { asm volatile("mbarrier.arrive.expect_tx.shared::cta.b64 _, [%0], %1;" ::"r"(bar), "r"(bytes) : "memory"); }
__device__ __forceinline__ void mbar_arrive(uint32_t bar) { asm volatile("mbarrier.arrive.shared::cta.b64 _, [%0];" ::"r"(bar) : "memory"); }
__device__ __forceinline__ bool mbar_try(uint32_t bar, uint32_t par) {
  uint32_t ok;
  asm volatile("{\n.reg .pred p;\nmbarrier.try_wait.parity.shared::cta.b64 p, [%1], %2;\nselp.u32 %0,1,0,p;\n}" : "=r"(ok) : "r"(bar), "r"(par) : "memory");
  return ok;
}
__device__ __forceinline__ void mbar_wait_slow(uint32_t bar, uint32_t par) {
  long long t0 = clock64();
  while (!mbar_try(bar, par)) { if (clock64() - t0 > 400000000LL) __trap(); }
}
__device__ __forceinline__ void mbar_wait(uint32_t bar, uint32_t par) { if (!mbar_try(bar, par)) mbar_wait_slow(bar, par); }
__device__ __forceinline__ void poll_cnt(const unsigned* p, unsigned target) {
  long long t0 = clock64();
  while (true) {
    unsigned v;
    asm volatile("ld.acquire.gpu.global.u32 %0, [%1];" : "=r"(v) : "l"(p) : "memory");
    if (v >= target) break;
    if (clock64() - t0 > 400000000LL) __trap();
  }
}
__device__ __forceinline__ void red_release(unsigned* p) { asm volatile("red.release.gpu.global.add.u32 [%0], 1;" ::"l"(p) : "memory"); }
__device__ __forceinline__ void fence_async() { asm volatile("fence.proxy.async;" ::: "memory"); }
__device__ __forceinline__ void fence_async_smem() { asm volatile("fence.proxy.async.shared::cta;" ::: "memory"); }
__device__ __forceinline__ void tma_ld2(uint32_t dst, const CUtensorMap* m, int c0, int c1, uint32_t bar) {
  asm volatile("cp.async.bulk.tensor.2d.shared::cluster.global.mbarrier::complete_tx::bytes [%0], [%1, {%3, %4}], [%2];" ::"r"(dst), "l"(m), "r"(bar), "r"(c0), "r"(c1) : "memory");
}
__device__ __forceinline__ void tma_st2(const CUtensorMap* m, uint32_t src, int c0, int c1) {
  asm volatile("cp.async.bulk.tensor.2d.global.shared::cta.bulk_group [%0, {%2, %3}], [%1];" ::"l"(m), "r"(src), "r"(c0), "r"(c1) : "memory");
}
__device__ __forceinline__ void bulk_ld(uint32_t dst, const void* src, uint32_t bytes, uint32_t bar) {
  asm volatile("cp.async.bulk.shared::cluster.global.mbarrier::complete_tx::bytes [%0], [%1], %2, [%3];" ::"r"(dst), "l"(src), "r"(bytes), "r"(bar) : "memory");
}
__device__ __forceinline__ void bulk_commit() { asm volatile("cp.async.bulk.commit_group;" ::: "memory"); }
__device__ __forceinline__ void bulk_wait0() { asm volatile("cp.async.bulk.wait_group 0;" ::: "memory"); }
__device__ __forceinline__ void bulk_wait0_read() { asm volatile("cp.async.bulk.wait_group.read 0;" ::: "memory"); }
__device__ __forceinline__ void nbar(int id, int n) { asm volatile("bar.sync %0, %1;" ::"r"(id), "r"(n) : "memory"); }
__device__ __forceinline__ void wg_fence() { asm volatile("wgmma.fence.sync.aligned;" ::: "memory"); }
__device__ __forceinline__ void wg_commit() { asm volatile("wgmma.commit_group.sync.aligned;" ::: "memory"); }
template <int n> __device__ __forceinline__ void wg_wait() { asm volatile("wgmma.wait_group.sync.aligned %0;" ::"n"(n) : "memory"); }
__device__ __forceinline__ uint64_t mkdesc(uint32_t addr, uint32_t lbo, uint32_t sbo, uint32_t sw) {
  return (uint64_t)((addr >> 4) & 0x3fff) | ((uint64_t)(lbo >> 4) << 16) | ((uint64_t)(sbo >> 4) << 32) | ((uint64_t)sw << 62);
}
__device__ __forceinline__ void ldsm4(uint32_t* r, uint32_t a) { asm volatile("ldmatrix.sync.aligned.m8n8.x4.shared.b16 {%0,%1,%2,%3},[%4];" : "=r"(r[0]), "=r"(r[1]), "=r"(r[2]), "=r"(r[3]) : "r"(a) : "memory"); }
__device__ __forceinline__ void ldsm4t(uint32_t* r, uint32_t a) { asm volatile("ldmatrix.sync.aligned.m8n8.x4.trans.shared.b16 {%0,%1,%2,%3},[%4];" : "=r"(r[0]), "=r"(r[1]), "=r"(r[2]), "=r"(r[3]) : "r"(a) : "memory"); }
__device__ __forceinline__ void stsm4(uint32_t a, uint32_t r0, uint32_t r1, uint32_t r2, uint32_t r3) { asm volatile("stmatrix.sync.aligned.m8n8.x4.shared.b16 [%0],{%1,%2,%3,%4};" ::"r"(a), "r"(r0), "r"(r1), "r"(r2), "r"(r3) : "memory"); }
__device__ __forceinline__ void stsm4t(uint32_t a, uint32_t r0, uint32_t r1, uint32_t r2, uint32_t r3) { asm volatile("stmatrix.sync.aligned.m8n8.x4.trans.shared.b16 [%0],{%1,%2,%3,%4};" ::"r"(a), "r"(r0), "r"(r1), "r"(r2), "r"(r3) : "memory"); }
__device__ __forceinline__ uint32_t lds32(uint32_t a) { uint32_t v; asm volatile("ld.shared.u32 %0,[%1];" : "=r"(v) : "r"(a) : "memory"); return v; }
__device__ __forceinline__ float ldsf(uint32_t a) { float v; asm volatile("ld.shared.f32 %0,[%1];" : "=f"(v) : "r"(a) : "memory"); return v; }
__device__ __forceinline__ float2 lds64f(uint32_t a) { float2 v; asm volatile("ld.shared.v2.f32 {%0,%1},[%2];" : "=f"(v.x), "=f"(v.y) : "r"(a) : "memory"); return v; }
__device__ __forceinline__ float4 lds128f(uint32_t a) { float4 v; asm volatile("ld.shared.v4.f32 {%0,%1,%2,%3},[%4];" : "=f"(v.x), "=f"(v.y), "=f"(v.z), "=f"(v.w) : "r"(a) : "memory"); return v; }
__device__ __forceinline__ uint4 lds128(uint32_t a) { uint4 v; asm volatile("ld.shared.v4.u32 {%0,%1,%2,%3},[%4];" : "=r"(v.x), "=r"(v.y), "=r"(v.z), "=r"(v.w) : "r"(a) : "memory"); return v; }
__device__ __forceinline__ void sts32(uint32_t a, uint32_t v) { asm volatile("st.shared.u32 [%0],%1;" ::"r"(a), "r"(v) : "memory"); }
__device__ __forceinline__ void stsf(uint32_t a, float v) { asm volatile("st.shared.f32 [%0],%1;" ::"r"(a), "f"(v) : "memory"); }
__device__ __forceinline__ void sts64f(uint32_t a, float x, float y) { asm volatile("st.shared.v2.f32 [%0],{%1,%2};" ::"r"(a), "f"(x), "f"(y) : "memory"); }
__device__ __forceinline__ void sts128f(uint32_t a, float x, float y, float z, float w) { asm volatile("st.shared.v4.f32 [%0],{%1,%2,%3,%4};" ::"r"(a), "f"(x), "f"(y), "f"(z), "f"(w) : "memory"); }
__device__ __forceinline__ void sts128(uint32_t a, uint32_t x, uint32_t y, uint32_t z, uint32_t w) { asm volatile("st.shared.v4.u32 [%0],{%1,%2,%3,%4};" ::"r"(a), "r"(x), "r"(y), "r"(z), "r"(w) : "memory"); }
__device__ __forceinline__ uint32_t pk(float lo, float hi) { uint32_t r; asm("cvt.rn.bf16x2.f32 %0,%1,%2;" : "=r"(r) : "f"(hi), "f"(lo)); return r; }
__device__ __forceinline__ float blo(uint32_t v) { return __uint_as_float(v << 16); }
__device__ __forceinline__ float bhi(uint32_t v) { return __uint_as_float(v & 0xffff0000u); }
__device__ __forceinline__ float bfr(float x) { return __bfloat162float(__float2bfloat16_rn(x)); }
__device__ __forceinline__ float ex2(float x) { float r; asm("ex2.approx.ftz.f32 %0,%1;" : "=f"(r) : "f"(x)); return r; }
__device__ __forceinline__ float red2pi(float x) {
  float k = rintf(x * 0.15915494309189535f);
  x = fmaf(k, -6.2831854820251465f, x);
  return fmaf(k, 1.7484555e-7f, x);
}
__device__ __forceinline__ float2 cmul(float2 a, float2 b) { return make_float2(fmaf(a.x, b.x, -a.y * b.y), fmaf(a.x, b.y, a.y * b.x)); }
__device__ __forceinline__ float2 cexp_p(float arl, float ai, float p) {
  float m = ex2(arl * p), ph = red2pi(ai * p);
  return make_float2(m * __cosf(ph), m * __sinf(ph));
}
__device__ __forceinline__ void wg_ss176(float* d, uint64_t da, uint64_t db, int sc){
  asm volatile("{\n.reg .pred p;\nsetp.ne.b32 p,%90,0;\nwgmma.mma_async.sync.aligned.m64n176k16.f32.bf16.bf16 {%0,%1,%2,%3,%4,%5,%6,%7,%8,%9,%10,%11,%12,%13,%14,%15,%16,%17,%18,%19,%20,%21,%22,%23,%24,%25,%26,%27,%28,%29,%30,%31,%32,%33,%34,%35,%36,%37,%38,%39,%40,%41,%42,%43,%44,%45,%46,%47,%48,%49,%50,%51,%52,%53,%54,%55,%56,%57,%58,%59,%60,%61,%62,%63,%64,%65,%66,%67,%68,%69,%70,%71,%72,%73,%74,%75,%76,%77,%78,%79,%80,%81,%82,%83,%84,%85,%86,%87},%88,%89,p,1,1,0,1;\n}"
    : "+f"(d[0]),"+f"(d[1]),"+f"(d[2]),"+f"(d[3]),"+f"(d[4]),"+f"(d[5]),"+f"(d[6]),"+f"(d[7]),"+f"(d[8]),"+f"(d[9]),"+f"(d[10]),"+f"(d[11]),"+f"(d[12]),"+f"(d[13]),"+f"(d[14]),"+f"(d[15]),"+f"(d[16]),"+f"(d[17]),"+f"(d[18]),"+f"(d[19]),"+f"(d[20]),"+f"(d[21]),"+f"(d[22]),"+f"(d[23]),"+f"(d[24]),"+f"(d[25]),"+f"(d[26]),"+f"(d[27]),"+f"(d[28]),"+f"(d[29]),"+f"(d[30]),"+f"(d[31]),"+f"(d[32]),"+f"(d[33]),"+f"(d[34]),"+f"(d[35]),"+f"(d[36]),"+f"(d[37]),"+f"(d[38]),"+f"(d[39]),"+f"(d[40]),"+f"(d[41]),"+f"(d[42]),"+f"(d[43]),"+f"(d[44]),"+f"(d[45]),"+f"(d[46]),"+f"(d[47]),"+f"(d[48]),"+f"(d[49]),"+f"(d[50]),"+f"(d[51]),"+f"(d[52]),"+f"(d[53]),"+f"(d[54]),"+f"(d[55]),"+f"(d[56]),"+f"(d[57]),"+f"(d[58]),"+f"(d[59]),"+f"(d[60]),"+f"(d[61]),"+f"(d[62]),"+f"(d[63]),"+f"(d[64]),"+f"(d[65]),"+f"(d[66]),"+f"(d[67]),"+f"(d[68]),"+f"(d[69]),"+f"(d[70]),"+f"(d[71]),"+f"(d[72]),"+f"(d[73]),"+f"(d[74]),"+f"(d[75]),"+f"(d[76]),"+f"(d[77]),"+f"(d[78]),"+f"(d[79]),"+f"(d[80]),"+f"(d[81]),"+f"(d[82]),"+f"(d[83]),"+f"(d[84]),"+f"(d[85]),"+f"(d[86]),"+f"(d[87])
    : "l"(da),"l"(db),"r"(sc));
}
__device__ __forceinline__ void wg_ss64(float* d, uint64_t da, uint64_t db, int sc){
  asm volatile("{\n.reg .pred p;\nsetp.ne.b32 p,%34,0;\nwgmma.mma_async.sync.aligned.m64n64k16.f32.bf16.bf16 {%0,%1,%2,%3,%4,%5,%6,%7,%8,%9,%10,%11,%12,%13,%14,%15,%16,%17,%18,%19,%20,%21,%22,%23,%24,%25,%26,%27,%28,%29,%30,%31},%32,%33,p,1,1,0,1;\n}"
    : "+f"(d[0]),"+f"(d[1]),"+f"(d[2]),"+f"(d[3]),"+f"(d[4]),"+f"(d[5]),"+f"(d[6]),"+f"(d[7]),"+f"(d[8]),"+f"(d[9]),"+f"(d[10]),"+f"(d[11]),"+f"(d[12]),"+f"(d[13]),"+f"(d[14]),"+f"(d[15]),"+f"(d[16]),"+f"(d[17]),"+f"(d[18]),"+f"(d[19]),"+f"(d[20]),"+f"(d[21]),"+f"(d[22]),"+f"(d[23]),"+f"(d[24]),"+f"(d[25]),"+f"(d[26]),"+f"(d[27]),"+f"(d[28]),"+f"(d[29]),"+f"(d[30]),"+f"(d[31])
    : "l"(da),"l"(db),"r"(sc));
}
template<int SC> __device__ __forceinline__ void wg_rs32(float* d, uint32_t a0, uint32_t a1, uint32_t a2, uint32_t a3, uint64_t db){
  asm volatile("wgmma.mma_async.sync.aligned.m64n32k16.f32.bf16.bf16 {%0,%1,%2,%3,%4,%5,%6,%7,%8,%9,%10,%11,%12,%13,%14,%15},{%16,%17,%18,%19},%20,%21,1,1,0;"
    : "+f"(d[0]),"+f"(d[1]),"+f"(d[2]),"+f"(d[3]),"+f"(d[4]),"+f"(d[5]),"+f"(d[6]),"+f"(d[7]),"+f"(d[8]),"+f"(d[9]),"+f"(d[10]),"+f"(d[11]),"+f"(d[12]),"+f"(d[13]),"+f"(d[14]),"+f"(d[15])
    : "r"(a0),"r"(a1),"r"(a2),"r"(a3),"l"(db),"n"(SC));
}
template<int SC> __device__ __forceinline__ void wg_rs16(float* d, uint32_t a0, uint32_t a1, uint32_t a2, uint32_t a3, uint64_t db){
  asm volatile("wgmma.mma_async.sync.aligned.m64n16k16.f32.bf16.bf16 {%0,%1,%2,%3,%4,%5,%6,%7},{%8,%9,%10,%11},%12,%13,1,1,0;"
    : "+f"(d[0]),"+f"(d[1]),"+f"(d[2]),"+f"(d[3]),"+f"(d[4]),"+f"(d[5]),"+f"(d[6]),"+f"(d[7])
    : "r"(a0),"r"(a1),"r"(a2),"r"(a3),"l"(db),"n"(SC));
}
template<int SC> __device__ __forceinline__ void wg_rs8(float* d, uint32_t a0, uint32_t a1, uint32_t a2, uint32_t a3, uint64_t db){
  asm volatile("wgmma.mma_async.sync.aligned.m64n8k16.f32.bf16.bf16 {%0,%1,%2,%3},{%4,%5,%6,%7},%8,%9,1,1,0;"
    : "+f"(d[0]),"+f"(d[1]),"+f"(d[2]),"+f"(d[3])
    : "r"(a0),"r"(a1),"r"(a2),"r"(a3),"l"(db),"n"(SC));
}

struct Params {
  const bf16 *x, *a_re, *a_im, *b_re, *b_im, *c_re, *c_im, *log_dt, *dskip, *w1, *w2;
};

__device__ __forceinline__ float kv_at(uint32_t kv, int v) {
  int j, c;
  if (v < 256) { j = v >> 2; c = v & 3; }
  else if (v < 512) { j = (v - 256) >> 2; c = 4 + ((v >> 1) & 1); }
  else { j = (v & 255) >> 2; c = 4 + (v >> 8); }
  return ldsf(kv + (j * 16 + c) * 4);
}
__device__ __forceinline__ float kd_at(uint32_t kv, int l, float dsk) {
  if (l < 0 || l > 510) return 0.f;
  int v = (int)bfr((float)l);
  float r = kv_at(kv, v);
  if (l == 0) r += dsk;
  if (l == 510) r -= kv_at(kv, 512);
  return r;
}

__device__ __forceinline__ void finish_arrive() {
  unsigned d = atomicAdd(&g_cnt[CNT_DONE], 1);
  if (d == 255) {
    g_cnt[CNT_PREP] = 0;
    for (int i = 0; i < 16; i++) g_cnt[CNT_H(i)] = 0;
    for (int i = 0; i < 8; i++) g_cnt[CNT_Y(i)] = 0;
    g_cnt[CNT_DONE] = 0;
  }
}

__global__ void __launch_bounds__(512, 1)
fused_kernel(const __grid_constant__ CUtensorMap tmX, const __grid_constant__ CUtensorMap tmW1,
             const __grid_constant__ CUtensorMap tmHst, const __grid_constant__ CUtensorMap tmHld,
             const __grid_constant__ CUtensorMap tmW2, const __grid_constant__ CUtensorMap tmYst,
             const __grid_constant__ CUtensorMap tmYld, const __grid_constant__ CUtensorMap tmOut, const Params P) {
  extern __shared__ __align__(1024) unsigned char smem_raw[];
  const uint32_t sb = smem_u32(smem_raw);
  const int tid = threadIdx.x, warp = tid >> 5, lane = tid & 31;
  const int b = blockIdx.x, mi = b >> 3, nj = b & 7;
  const uint32_t bars = sb + SM_BAR;
#define BAR(i) (bars + 8 * (i))

  if (warp < 8) {
    const bool prod = (tid == 128);
    if (prod) {
      if (sb & 1023) __trap();
      for (int i = 0; i < 4; i++) { mbar_init(BAR(B_F1 + i), 1); mbar_init(BAR(B_E1 + i), 8); }
      for (int i = 0; i < 6; i++) { mbar_init(BAR(B_F2 + i), 1); mbar_init(BAR(B_E2 + i), 8); }
      for (int i = B_MISC; i <= B_Y; i++) mbar_init(BAR(i), 1);
      asm volatile("fence.mbarrier_init.release.cluster;" ::: "memory");
      fence_async_smem();
      for (int ks = 0; ks < 4; ks++) {
        uint32_t slot = sb + ks * 40960;
        mbar_expect(BAR(B_F1 + ks), 40960);
        tma_ld2(slot, &tmX, 64 * ks, 128 * mi, BAR(B_F1 + ks));
        for (int a = 0; a < 3; a++) tma_ld2(slot + 16384 + 8192 * a, &tmW1, 176 * nj + 64 * a, 64 * ks, BAR(B_F1 + ks));
      }
      asm volatile("cp.async.bulk.prefetch.L2.global [%0], %1;" ::"l"((const char*)P.w2 + 11008 * b), "r"(11008) : "memory");
    }
    __syncthreads();
    const int wg = warp >> 2, g = lane >> 2, q = lane & 3;
    {
      float acc[88];
#pragma unroll 1
      for (int ks = 0; ks < 8; ks++) {
        const int s = ks & 3;
        mbar_wait(BAR(B_F1 + s), ks >> 2);
        if (ks == 0) TS(0 + wg);
        const uint32_t slot = sb + s * 40960;
        const uint64_t da = mkdesc(slot + wg * 8192, 16, 1024, 1);
        const uint64_t db = mkdesc(slot + 16384, 8192, 1024, 1);
        wg_fence();
#pragma unroll
        for (int k = 0; k < 4; k++) wg_ss176(acc, da + 2 * k, db + 128 * k, (ks | k) != 0);
        wg_commit();
        if (ks > 0) {
          wg_wait<1>();
          const int sp = (ks - 1) & 3;
          if (lane == 0) mbar_arrive(BAR(B_E1 + sp));
          if (prod && ks < 7) {
            mbar_wait(BAR(B_E1 + sp), (ks - 1) >> 2);
            if (ks < 5) {
              const uint32_t sl = sb + sp * 40960;
              mbar_expect(BAR(B_F1 + sp), 40960);
              tma_ld2(sl, &tmX, 64 * (ks + 3), 128 * mi, BAR(B_F1 + sp));
              for (int a = 0; a < 3; a++) tma_ld2(sl + 16384 + 8192 * a, &tmW1, 176 * nj + 64 * a, 64 * (ks + 3), BAR(B_F1 + sp));
            } else {
              for (int kk = 2 * sp; kk < 2 * sp + 2; kk++) {
                mbar_expect(BAR(B_F2 + kk), 24576);
                tma_ld2(sb + kk * 24576, &tmW2, 64 * nj, 64 * kk, BAR(B_F2 + kk));
              }
            }
          }
          __syncwarp();
        }
      }
      wg_wait<0>();
      if (lane == 0) mbar_arrive(BAR(B_E1 + 3));
      TS(2 + wg);
      mbar_wait(BAR(B_MISC), 0);
      mbar_wait(BAR(B_E1 + 2), 1);
      mbar_wait(BAR(B_E1 + 3), 1);
      const float2 st0 = lds64f(sb + SM_STAT + (16 * warp + g) * 8);
      const float2 st1 = lds64f(sb + SM_STAT + (16 * warp + g + 8) * 8);
      const uint32_t hst = sb + SM_HST + warp * 5632;
      const uint32_t sta = hst + ((lane & 7) + 8 * ((lane >> 3) & 1)) * 352 + (lane >> 4) * 16;
#pragma unroll
      for (int i = 0; i < 22; i += 2) {
        uint32_t r[4];
#pragma unroll
        for (int u = 0; u < 2; u++) {
          const float2 cs = lds64f(sb + SM_COLS + (8 * (i + u) + 2 * q) * 4);
          const float* a = acc + 4 * (i + u);
          r[2 * u] = pk(fmaxf(fmaf(a[0], st0.x, -st0.y * cs.x), 0.f), fmaxf(fmaf(a[1], st0.x, -st0.y * cs.y), 0.f));
          r[2 * u + 1] = pk(fmaxf(fmaf(a[2], st1.x, -st1.y * cs.x), 0.f), fmaxf(fmaf(a[3], st1.x, -st1.y * cs.y), 0.f));
        }
        stsm4(sta + i * 16, r[0], r[1], r[2], r[3]);
      }
      fence_async_smem();
      __syncwarp();
      if (lane == 0) {
        tma_st2(&tmHst, hst, 176 * nj, 128 * mi + 16 * warp);
        bulk_commit();
        bulk_wait0();
        fence_async();
        __threadfence();
        red_release(&g_cnt[CNT_H(mi)]);
        if (prod) {
          poll_cnt(&g_cnt[CNT_H(mi)], 64);
          TS1(18);
          fence_async();
          for (int kk = 0; kk < 6; kk++) {
            if (kk >= 4) {
              mbar_expect(BAR(B_F2 + kk), 24576);
              tma_ld2(sb + kk * 24576, &tmW2, 64 * nj, 64 * kk, BAR(B_F2 + kk));
            }
            tma_ld2(sb + kk * 24576 + 8192, &tmHld, 64 * kk, 128 * mi, BAR(B_F2 + kk));
          }
          mbar_expect(BAR(B_X), 16384);
          tma_ld2(sb + SM_XT, &tmX, 64 * nj, 128 * mi, BAR(B_X));
          finish_arrive();
        }
      }
      __syncwarp();
      TS(4 + wg);
    }
    {
      float acc[32];
      int s = 0, ph = 0, sp = 0, spp = 0, php = 0, phpp = 0;
#pragma unroll 1
      for (int kk = 0; kk < 22; kk++) {
        mbar_wait(BAR(B_F2 + s), ph);
        if (kk == 0) TS(6 + wg);
        const uint32_t slot = sb + s * 24576;
        const uint64_t da = mkdesc(slot + 8192 + wg * 8192, 16, 1024, 1);
        const uint64_t db = mkdesc(slot, 8192, 1024, 1);
        wg_fence();
        wg_ss64(acc, da, db, kk != 0);
        wg_ss64(acc, da + 2, db + 128, 1);
        if (kk < 21) {
          wg_ss64(acc, da + 4, db + 256, 1);
          wg_ss64(acc, da + 6, db + 384, 1);
        }
        wg_commit();
        if (kk > 0) {
          wg_wait<1>();
          if (lane == 0) mbar_arrive(BAR(B_E2 + sp));
          if (prod && kk >= 2 && kk < 18) {
            mbar_wait(BAR(B_E2 + spp), phpp);
            mbar_expect(BAR(B_F2 + spp), 24576);
            tma_ld2(sb + spp * 24576, &tmW2, 64 * nj, 64 * (kk + 4), BAR(B_F2 + spp));
            tma_ld2(sb + spp * 24576 + 8192, &tmHld, 64 * (kk + 4), 128 * mi, BAR(B_F2 + spp));
          }
          __syncwarp();
        }
        spp = sp; phpp = php;
        sp = s; php = ph;
        if (++s == 6) { s = 0; ph ^= 1; }
      }
      wg_wait<0>();
      TS(8 + wg);
      mbar_wait(BAR(B_X), 0);
      mbar_wait(BAR(B_Y), 0);
      const int mu = lane >> 3, r = lane & 7;
      const uint32_t xa = sb + SM_XT + (16 * warp + r + 8 * (mu & 1)) * 128;
      const uint32_t ya = sb + SM_U + (warp >> 2) * 8192 + (8 * (mu >> 1) + r) * 128 + (((2 * (warp & 3) + (mu & 1)) ^ r) << 4);
#pragma unroll
      for (int i = 0; i < 8; i += 2) {
        uint32_t xv[4], yv[4], o[4];
        const uint32_t xadr = xa + (((i + (mu >> 1)) ^ r) << 4);
        ldsm4(xv, xadr);
        ldsm4t(yv, ya + i * 1024);
#pragma unroll
        for (int u = 0; u < 4; u++) {
          const float* a = acc + 4 * (i + (u >> 1)) + 2 * (u & 1);
          o[u] = pk(a[0] + blo(xv[u]) + blo(yv[u]), a[1] + bhi(xv[u]) + bhi(yv[u]));
        }
        stsm4(xadr, o[0], o[1], o[2], o[3]);
      }
      fence_async_smem();
      __syncwarp();
      if (lane == 0) {
        tma_st2(&tmOut, sb + SM_XT + warp * 2048, 64 * nj, 128 * mi + 16 * warp);
        bulk_commit();
        bulk_wait0_read();
      }
      TS(10 + wg);
    }
  } else {
    const int st = tid - 256, wg = st >> 7, t128 = st & 127, w = (st >> 5) & 3, sw = st >> 5;
    const int g = lane >> 2, q = lane & 3;
    uint32_t xr[16];
    {
      const uint32_t* xp = reinterpret_cast<const uint32_t*>(P.x) + (size_t)(128 * mi + 8 * nj) * 256 + st;
#pragma unroll
      for (int r = 0; r < 16; r++) xr[r] = __ldg(xp + ((r >> 3) * 64 + (r & 7)) * 256);
    }
    uint4 wc[4];
    if (b < 86) {
      const uint4* wp = reinterpret_cast<const uint4*>(P.w1 + (size_t)(2 * st) * 1376 + 16 * b);
      wc[0] = __ldg(wp); wc[1] = __ldg(wp + 1); wc[2] = __ldg(wp + 172); wc[3] = __ldg(wp + 173);
    } else {
      wc[0] = wc[1] = wc[2] = wc[3] = make_uint4(0, 0, 0, 0);
    }
    float prm[2][8];
#pragma unroll
    for (int c = 0; c < 2; c++) {
      const int ch = 4 * b + 2 * wg + c, ix = ch * 128 + t128;
      prm[c][0] = __bfloat162float(P.a_re[ix]); prm[c][1] = __bfloat162float(P.a_im[ix]);
      prm[c][2] = __bfloat162float(P.b_re[ix]); prm[c][3] = __bfloat162float(P.b_im[ix]);
      prm[c][4] = __bfloat162float(P.c_re[ix]); prm[c][5] = __bfloat162float(P.c_im[ix]);
      prm[c][6] = __bfloat162float(P.log_dt[ch]); prm[c][7] = __bfloat162float(P.dskip[ch]);
    }
    sts128(sb + SM_U + (st >> 6) * U_CH + ((st >> 3) & 7) * U_PL + (st & 7) * 16, 0, 0, 0, 0);
    fence_async_smem();
    __syncthreads();
    {
      const uint32_t red = sb + SM_KT, cred = red + 1024, wst = red + 2048 + sw * 128;
      float v[32];
#pragma unroll
      for (int r = 0; r < 16; r++) {
        const float a = blo(xr[r]), c = bhi(xr[r]);
        v[r] = a + c;
        v[16 + r] = fmaf(a, a, c * c);
      }
#pragma unroll
      for (int off = 16; off >= 1; off >>= 1) {
        const bool up = lane & off;
#pragma unroll
        for (int i = 0; i < off; i++) {
          const float snd = up ? v[i] : v[i + off], kp = up ? v[i + off] : v[i];
          v[i] = kp + __shfl_xor_sync(0xffffffffu, snd, off);
        }
      }
      stsf(red + (sw * 32 + lane) * 4, v[0]);
      float cv[16];
      {
#pragma unroll
        for (int i = 0; i < 8; i++) {
          const uint32_t a = i < 4 ? (&wc[0].x)[i] : (&wc[1].x)[i - 4], c = i < 4 ? (&wc[2].x)[i] : (&wc[3].x)[i - 4];
          cv[2 * i] = blo(a) + blo(c);
          cv[2 * i + 1] = bhi(a) + bhi(c);
        }
      }
#pragma unroll
      for (int off = 8; off >= 1; off >>= 1) {
        const bool up = lane & off;
#pragma unroll
        for (int i = 0; i < off; i++) {
          const float snd = up ? cv[i] : cv[i + off], kp = up ? cv[i + off] : cv[i];
          cv[i] = kp + __shfl_xor_sync(0xffffffffu, snd, off);
        }
      }
      cv[0] += __shfl_xor_sync(0xffffffffu, cv[0], 16);
      if (lane < 16) stsf(cred + (sw * 16 + lane) * 4, cv[0]);
      nbar(1, 256);
      float tot = 0.f;
#pragma unroll
      for (int i = 0; i < 8; i++) tot += ldsf(red + (i * 32 + lane) * 4);
      const float oth = __shfl_xor_sync(0xffffffffu, tot, 16);
      if (lane < 16) {
        const float mean = tot * (1.f / 512.f);
        const float var = fmaxf(fmaf(-mean, mean, oth * (1.f / 512.f)), 0.f);
        const float mb = bfr(mean);
        const float den = bfr(sqrtf(bfr(bfr(var) + 1e-5f)));
        const float rs = 1.f / den;
        sts64f(wst + lane * 8, mb, rs);
        if (sw == 0) g_stat[128 * mi + 64 * (lane >> 3) + 8 * nj + (lane & 7)] = make_float2(rs, mb * rs);
      }
      if (sw == 1 && lane < 16 && b < 86) {
        float cs = 0.f;
#pragma unroll
        for (int i = 0; i < 8; i++) cs += ldsf(cred + (i * 16 + lane) * 4);
        g_colsum[16 * b + lane] = cs;
      }
      __syncwarp();
      uint32_t o0[8], o1[8];
#pragma unroll
      for (int r = 0; r < 16; r += 2) {
        const float4 s2 = lds128f(wst + r * 8);
        o0[r >> 1] = pk(bfr(blo(xr[r]) - s2.x) * s2.y, bfr(blo(xr[r + 1]) - s2.z) * s2.w);
        o1[r >> 1] = pk(bfr(bhi(xr[r]) - s2.x) * s2.y, bfr(bhi(xr[r + 1]) - s2.z) * s2.w);
      }
      uint4* dp = reinterpret_cast<uint4*>(g_xnP + (size_t)(2 * st) * 2048 + nj * 256 + mi * 16);
      dp[0] = make_uint4(o0[0], o0[1], o0[2], o0[3]);
      dp[1] = make_uint4(o0[4], o0[5], o0[6], o0[7]);
      dp[256] = make_uint4(o1[0], o1[1], o1[2], o1[3]);
      dp[257] = make_uint4(o1[4], o1[5], o1[6], o1[7]);
      fence_async();
      nbar(1, 256);
      if (st == 0) { __threadfence(); red_release(&g_cnt[CNT_PREP]); }
    }
    if (wg == 0) TS(12);
    const uint32_t wk = sb + SM_WORK + wg * WK_SZ;
    float k1024[2];
#pragma unroll
    for (int c = 0; c < 2; c++) {
      {
        const float dt = bfr(expf(prm[c][6]));
        const float ar = dt * prm[c][0], ai = dt * prm[c][1];
        const float arl = ar * 1.4426950408889634f;
        const float2 cp = cmul(make_float2(prm[c][4], prm[c][5]), make_float2(dt * prm[c][2], dt * prm[c][3]));
        const float2 z1 = cexp_p(arl, ai, 1.f), z32 = cexp_p(arl, ai, 32.f), z256 = cexp_p(arl, ai, 256.f);
        sts128f(wk + WK_PRM + t128 * 16, 4.f * arl, red2pi(4.f * ai), z32.x, z32.y);
        const uint32_t bt = wk + WK_BT + (t128 >> 2) * 272 + (t128 & 3) * 4;
        const float2 w1 = cmul(cp, z1), w2 = cmul(w1, z1), w3 = cmul(w2, z1);
        sts32(bt + 0 * 16, pk(cp.x, -cp.y));
        sts32(bt + 1 * 16, pk(w1.x, -w1.y));
        sts32(bt + 2 * 16, pk(w2.x, -w2.y));
        sts32(bt + 3 * 16, pk(w3.x, -w3.y));
        float2 wv = cmul(cp, z256);
        sts32(bt + 4 * 16, pk(wv.x, -wv.y));
        const float2 w258 = cmul(w2, z256);
        sts32(bt + 5 * 16, pk(w258.x, -w258.y));
#pragma unroll
        for (int i = 6; i <= 12; i++) {
          wv = cmul(wv, z256);
          sts32(bt + i * 16, pk(wv.x, -wv.y));
        }
      }
      fence_async_smem();
      nbar(2 + wg, 128);
      float ka[8];
      const float jf = (float)(16 * w + g);
      const uint64_t dbt = mkdesc(wk + WK_BT, 272, 128, 0);
#pragma unroll
      for (int k4 = 0; k4 < 4; k4++) {
        uint32_t af[4][4];
#pragma unroll
        for (int k = 0; k < 4; k++) {
#pragma unroll
          for (int hh = 0; hh < 2; hh++) {
            const float4 p = lds128f(wk + WK_PRM + (8 * (4 * k4 + k) + 4 * hh + q) * 16);
            const float m = ex2(p.x * jf), ph = p.y * jf;
            const float2 e = make_float2(m * __cosf(ph), m * __sinf(ph));
            const float2 e8 = cmul(e, make_float2(p.z, p.w));
            af[k][2 * hh] = pk(e.x, e.y);
            af[k][2 * hh + 1] = pk(e8.x, e8.y);
          }
        }
        wg_fence();
#pragma unroll
        for (int k = 0; k < 4; k++) {
          if (k4 == 0 && k == 0) wg_rs16<0>(ka, af[k][0], af[k][1], af[k][2], af[k][3], dbt);
          else wg_rs16<1>(ka, af[k][0], af[k][1], af[k][2], af[k][3], dbt + (4 * k4 + k) * 34);
        }
        wg_commit();
      }
      wg_wait<0>();
      const uint32_t kv = wk + WK_KV;
      sts64f(kv + ((16 * w + g) * 16 + 2 * q) * 4, ka[0], ka[1]);
      sts64f(kv + ((16 * w + g + 8) * 16 + 2 * q) * 4, ka[2], ka[3]);
      sts64f(kv + ((16 * w + g) * 16 + 8 + 2 * q) * 4, ka[4], ka[5]);
      sts64f(kv + ((16 * w + g + 8) * 16 + 8 + 2 * q) * 4, ka[6], ka[7]);
      nbar(2 + wg, 128);
      const uint32_t kt = sb + SM_KT + (2 * wg + c) * KT_CH;
      unsigned pv = 0;
      if (c == 0 && st == 0) asm volatile("ld.relaxed.gpu.global.u32 %0, [%1];" : "=r"(pv) : "l"(&g_cnt[CNT_PREP]) : "memory");
#pragma unroll 1
      for (int y = t128; y < 640; y += 128) sts32(kt + y * 4, pk(kd_at(kv, y - 64, prm[c][7]), kd_at(kv, y - 65, prm[c][7])));
      if (t128 < 96) {
        float e[2];
#pragma unroll
        for (int u = 0; u < 2; u++) { const int m = 2 * t128 + u; e[u] = (m >= 64 && m <= 128) ? kv_at(kv, 8 * m) : 0.f; }
        sts32(kt + KT_Z5 + t128 * 4, pk(e[0], e[1]));
#pragma unroll
        for (int u = 0; u < 2; u++) { const int m = 2 * t128 + u; e[u] = (m >= 64 && m <= 127) ? kv_at(kv, 8 * m + 4) : 0.f; }
        sts32(kt + KT_Z3 + t128 * 4, pk(e[0], e[1]));
#pragma unroll
        for (int u = 0; u < 2; u++) { const int m = 2 * t128 + u + 73; e[u] = (m >= 129 && m <= 256) ? kv_at(kv, 8 * m) : 0.f; }
        sts32(kt + KT_Z4 + t128 * 4, pk(e[0], e[1]));
      }
      k1024[c] = kv_at(kv, 1024);
      if (c == 0 && sw == 0) {
        if (lane == 0) {
          if (pv < 128) poll_cnt(&g_cnt[CNT_PREP], 128);
          __threadfence();
          TS1(17);
          fence_async();
          mbar_expect(BAR(B_MISC), 1024 + 704);
          bulk_ld(sb + SM_STAT, g_stat + 128 * mi, 1024, BAR(B_MISC));
          bulk_ld(sb + SM_COLS, g_colsum + 176 * nj, 704, BAR(B_MISC));
          mbar_expect(BAR(B_U), 16384);
        }
        __syncwarp();
        fence_async();
        bulk_ld(sb + SM_U + (lane >> 3) * U_CH + (lane & 7) * U_PL + 128, g_xnP + (size_t)(4 * b * 8 + lane) * 256, 512, BAR(B_U));
      }
      fence_async_smem();
      nbar(2 + wg, 128);
    }
    if (wg == 0) TS(13);
    mbar_wait(BAR(B_U), 0);
#pragma unroll 1
    for (int c = 0; c < 2; c++) {
      const uint32_t ub = sb + SM_U + (2 * wg + c) * U_CH;
      const uint32_t kt = sb + SM_KT + (2 * wg + c) * KT_CH;
#pragma unroll 1
      for (int ci = t128 - 23; ci <= 191; ci += 128) {
        float u[24];
#pragma unroll
        for (int k = 0; k < 3; k++) {
          const int cc = ci - 1 + k;
          const uint4 vv = lds128(ub + (cc & 7) * U_PL + ((cc >> 3) + 8) * 16);
          u[8 * k + 0] = blo(vv.x); u[8 * k + 1] = bhi(vv.x); u[8 * k + 2] = blo(vv.y); u[8 * k + 3] = bhi(vv.y);
          u[8 * k + 4] = blo(vv.z); u[8 * k + 5] = bhi(vv.z); u[8 * k + 6] = blo(vv.w); u[8 * k + 7] = bhi(vv.w);
        }
        float f2[8], s5[8];
#pragma unroll
        for (int i = 0; i < 8; i++) f2[i] = u[i + 4] + u[i + 5];
#pragma unroll
        for (int i = 0; i < 8; i++) s5[i] = (u[i + 6] + u[i + 7]) + (u[i + 8] + u[i + 9]) + u[i + 10];
        sts128(wk + WK_S5 + (ci + 23) * 16, pk(s5[0], s5[1]), pk(s5[2], s5[3]), pk(s5[4], s5[5]), pk(s5[6], s5[7]));
        if (ci >= -7)
          sts128(wk + WK_S3 + (ci + 7) * 16, pk(f2[0] + u[3], f2[1] + u[4]), pk(f2[2] + u[5], f2[3] + u[6]), pk(f2[4] + u[7], f2[5] + u[8]),
                 pk(f2[6] + u[9], f2[7] + u[10]));
        if (ci >= -8 && ci <= 127) {
          float s7[8];
#pragma unroll
          for (int i = 0; i < 8; i++) s7[i] = s5[i] + (u[i + 5] + u[i + 11]);
          sts128(wk + WK_S7 + (ci + 8) * 16, pk(s7[0], s7[1]), pk(s7[2], s7[3]), pk(s7[4], s7[5]), pk(s7[6], s7[7]));
#pragma unroll
          for (int i = 0; i < 8; i++) s7[i] += (u[i + 4] + u[i + 12]);
          sts128(wk + WK_S9 + (ci + 8) * 16, pk(s7[0], s7[1]), pk(s7[2], s7[3]), pk(s7[4], s7[5]), pk(s7[6], s7[7]));
          if (ci >= 0) sts128(wk + WK_F + (ci & 7) * 272 + (ci >> 3) * 16, pk(f2[0], f2[1]), pk(f2[2], f2[3]), pk(f2[4], f2[5]), pk(f2[6], f2[7]));
        }
      }
      nbar(2 + wg, 128);
      if (c == 0) { if (wg == 0) TS(14); mbar_wait(BAR(B_E1 + 3), 1); }
      float dacc[16], e01[8], e12[8], e23[8], e3[4];
      {
        const uint32_t pa = kt + (16 * w + g - 2 * q + 520 + 64) * 4;
        uint32_t hprev = lds32(pa);
#pragma unroll
        for (int blk = 0; blk < 3; blk++) {
          uint32_t h[25];
          h[0] = hprev;
#pragma unroll
          for (int i = 1; i < 25; i++) h[i] = lds32(pa - (24 * blk + i) * 32);
          hprev = h[24];
          if (blk == 2) wg_wait<1>();
          wg_fence();
#pragma unroll
          for (int k = 0; k < 12; k++) {
            const int kap = 12 * blk + k;
            const uint64_t db = mkdesc(ub + (kap & 3) * 2 * U_PL + (kap >> 2) * 16, U_PL, 128, 0);
            if (kap == 0) wg_rs32<0>(dacc, h[2 * k + 1], h[2 * k], h[2 * k + 2], h[2 * k + 1], db);
            else wg_rs32<1>(dacc, h[2 * k + 1], h[2 * k], h[2 * k + 2], h[2 * k + 1], db);
          }
          wg_commit();
        }
      }
      {
        const int mu = lane >> 3, r = lane & 7, kk = r + 8 * (mu >> 1);
        const int cofs = 15 - kk + 2 * w + (mu & 1);
        const uint32_t a5 = wk + WK_S5 + cofs * 16;
        const uint32_t a3 = wk + WK_S3 + cofs * 16;
        const uint32_t a4 = wk + ((kk & 1) ? WK_S9 : WK_S7) + cofs * 16;
        uint32_t f[7][4];
        wg_wait<1>();
#pragma unroll
        for (int k = 0; k < 7; k++) ldsm4t(f[k], a5 + k * 256);
        wg_fence();
        wg_rs16<0>(e01, f[0][0], f[0][1], f[0][2], f[0][3], mkdesc(kt + KT_Z5 + 2 * (0 + 8), 16, 128, 0));
        wg_rs16<0>(e12, f[1][0], f[1][1], f[1][2], f[1][3], mkdesc(kt + KT_Z5 + 2 * (64 + 8 - 16), 16, 128, 0));
        wg_rs16<0>(e23, f[5][0], f[5][1], f[5][2], f[5][3], mkdesc(kt + KT_Z5 + 2 * (128 + 8 - 80), 16, 128, 0));
#pragma unroll
        for (int k = 2; k < 5; k++) wg_rs16<1>(e12, f[k][0], f[k][1], f[k][2], f[k][3], mkdesc(kt + KT_Z5 + 2 * (64 + 8 - 16 * k), 16, 128, 0));
        wg_rs16<1>(e23, f[6][0], f[6][1], f[6][2], f[6][3], mkdesc(kt + KT_Z5 + 2 * (128 + 8 - 96), 16, 128, 0));
        wg_commit();
        uint32_t f1[6][4];
        wg_wait<1>();
#pragma unroll
        for (int k = 0; k < 6; k++) ldsm4t(f1[k], a5 + (7 + k) * 256);
        wg_fence();
#pragma unroll
        for (int k = 0; k < 6; k++) {
          const int kap = 7 + k;
          if (kap <= 8) wg_rs16<1>(e23, f1[k][0], f1[k][1], f1[k][2], f1[k][3], mkdesc(kt + KT_Z5 + 2 * (128 + 8 - 16 * kap), 16, 128, 0));
          else if (kap == 9) wg_rs8<0>(e3, f1[k][0], f1[k][1], f1[k][2], f1[k][3], mkdesc(kt + KT_Z5 + 2 * (192 + 8 - 16 * kap), 16, 128, 0));
          else wg_rs8<1>(e3, f1[k][0], f1[k][1], f1[k][2], f1[k][3], mkdesc(kt + KT_Z5 + 2 * (192 + 8 - 16 * kap), 16, 128, 0));
        }
        wg_commit();
#pragma unroll
        for (int blk = 0; blk < 2; blk++) {
          uint32_t f3[6][4];
          wg_wait<1>();
#pragma unroll
          for (int k = 0; k < 6; k++) ldsm4t(f3[k], a3 + (6 * blk + k) * 256);
          wg_fence();
#pragma unroll
          for (int k = 0; k < 6; k++) {
            const int kap = 6 * blk + k;
            if (kap < 4) wg_rs16<1>(e12, f3[k][0], f3[k][1], f3[k][2], f3[k][3], mkdesc(kt + KT_Z3 + 2 * (64 - 8 - 16 * kap), 16, 128, 0));
            else if (kap < 8) wg_rs16<1>(e23, f3[k][0], f3[k][1], f3[k][2], f3[k][3], mkdesc(kt + KT_Z3 + 2 * (128 - 8 - 16 * kap), 16, 128, 0));
            else wg_rs8<1>(e3, f3[k][0], f3[k][1], f3[k][2], f3[k][3], mkdesc(kt + KT_Z3 + 2 * (192 - 8 - 16 * kap), 16, 128, 0));
          }
          wg_commit();
        }
#pragma unroll
        for (int blk = 0; blk < 2; blk++) {
          uint32_t f4[4][4];
          wg_wait<1>();
#pragma unroll
          for (int k = 0; k < 4; k++) ldsm4t(f4[k], a4 + (4 * blk + k) * 256);
          wg_fence();
#pragma unroll
          for (int k = 0; k < 4; k++) {
            const int kap = 4 * blk + k;
            if (kap < 4) wg_rs16<1>(e23, f4[k][0], f4[k][1], f4[k][2], f4[k][3], mkdesc(kt + KT_Z4 + 2 * (128 - 80 - 16 * kap), 16, 128, 0));
            else wg_rs8<1>(e3, f4[k][0], f4[k][1], f4[k][2], f4[k][3], mkdesc(kt + KT_Z4 + 2 * (192 - 80 - 16 * kap), 16, 128, 0));
          }
          wg_commit();
        }
        uint32_t ff[4];
        ldsm4t(ff, wk + WK_F + (2 * w + (mu & 1)) * 272 + (8 * (mu >> 1) + r) * 16);
        wg_wait<0>();
        const float kf = c ? k1024[1] : k1024[0];
#pragma unroll
        for (int i = 0; i < 4; i++) { dacc[i] += e01[i]; dacc[4 + i] += e01[4 + i] + e12[i]; dacc[8 + i] += e12[4 + i] + e23[i]; dacc[12 + i] += e23[4 + i] + e3[i]; }
#pragma unroll
        for (int u = 0; u < 4; u++) {
          dacc[8 + 2 * u] = fmaf(kf, blo(ff[u]), dacc[8 + 2 * u]);
          dacc[9 + 2 * u] = fmaf(kf, bhi(ff[u]), dacc[9 + 2 * u]);
        }
        nbar(2 + wg, 128);
#pragma unroll
        for (int i = 0; i < 4; i += 2) {
          const int n = 8 * (i + (mu >> 1)) + r;
          stsm4t(wk + n * 128 + (((2 * w + (mu & 1)) ^ r) << 4), pk(dacc[4 * i], dacc[4 * i + 1]), pk(dacc[4 * i + 2], dacc[4 * i + 3]),
                 pk(dacc[4 * i + 4], dacc[4 * i + 5]), pk(dacc[4 * i + 6], dacc[4 * i + 7]));
        }
        fence_async_smem();
        nbar(2 + wg, 128);
        if (t128 == 0) {
          tma_st2(&tmYst, wk, 0, (4 * b + 2 * wg + c) * 32);
          bulk_commit();
          if (c == 0) bulk_wait0_read();
          else { bulk_wait0(); fence_async(); __threadfence(); red_release(&g_cnt[CNT_Y(b >> 4)]); }
        }
        if (c == 0) nbar(2 + wg, 128);
      }
    }
    TS(21 + wg);
    nbar(1, 256);
    if (st == 0) {
      poll_cnt(&g_cnt[CNT_Y(nj)], 32);
      fence_async();
      mbar_expect(BAR(B_Y), 16384);
      tma_ld2(sb + SM_U, &tmYld, 128 * mi, 64 * nj, BAR(B_Y));
      tma_ld2(sb + SM_U + 8192, &tmYld, 128 * mi + 64, 64 * nj, BAR(B_Y));
      TS1(20);
      finish_arrive();
    }
  }
}

typedef CUresult (*PFN_enc)(CUtensorMap*, CUtensorMapDataType, cuuint32_t, void*, const cuuint64_t*, const cuuint64_t*, const cuuint32_t*,
                            const cuuint32_t*, CUtensorMapInterleave, CUtensorMapSwizzle, CUtensorMapL2promotion, CUtensorMapFloatOOBfill);

static void make_map(PFN_enc enc, CUtensorMap* m, const void* ptr, uint64_t cols, uint64_t rows, uint32_t bc, uint32_t br, bool sw) {
  cuuint64_t dims[2] = {cols, rows};
  cuuint64_t strides[1] = {cols * 2};
  cuuint32_t box[2] = {bc, br};
  cuuint32_t es[2] = {1, 1};
  enc(m, CU_TENSOR_MAP_DATA_TYPE_BFLOAT16, 2, const_cast<void*>(ptr), dims, strides, box, es, CU_TENSOR_MAP_INTERLEAVE_NONE,
      sw ? CU_TENSOR_MAP_SWIZZLE_128B : CU_TENSOR_MAP_SWIZZLE_NONE, CU_TENSOR_MAP_L2_PROMOTION_L2_128B, CU_TENSOR_MAP_FLOAT_OOB_FILL_NONE);
}

extern "C" void kernel_launch(void* const* d_in, const int* in_sizes, int n_in, void* d_out, int out_size) {
  (void)in_sizes; (void)n_in; (void)out_size;
  static PFN_enc enc = nullptr;
  static void *ph = nullptr, *py = nullptr;
  if (!enc) {
    void* fn = nullptr;
    cudaDriverEntryPointQueryResult qr;
    cudaGetDriverEntryPoint("cuTensorMapEncodeTiled", &fn, cudaEnableDefault, &qr);
    enc = (PFN_enc)fn;
    cudaGetSymbolAddress(&ph, g_h);
    cudaGetSymbolAddress(&py, g_yT);
    cudaFuncSetAttribute(fused_kernel, cudaFuncAttributeMaxDynamicSharedMemorySize, SM_TOTAL);
  }
  CUtensorMap tmX, tmW1, tmHst, tmHld, tmW2, tmYst, tmYld, tmOut;
  make_map(enc, &tmX, d_in[0], 512, 2048, 64, 128, true);
  make_map(enc, &tmW1, d_in[10], 1376, 512, 64, 64, true);
  make_map(enc, &tmHst, ph, 1376, 2048, 176, 16, false);
  make_map(enc, &tmHld, ph, 1376, 2048, 64, 128, true);
  make_map(enc, &tmW2, d_in[11], 512, 1376, 64, 64, true);
  make_map(enc, &tmYst, py, 64, 512 * 32, 64, 32, true);
  make_map(enc, &tmYld, py, 2048, 512, 64, 64, true);
  make_map(enc, &tmOut, d_out, 512, 2048, 64, 16, true);
  Params P;
  P.x = (const bf16*)d_in[0]; P.a_re = (const bf16*)d_in[1]; P.a_im = (const bf16*)d_in[2];
  P.b_re = (const bf16*)d_in[3]; P.b_im = (const bf16*)d_in[4]; P.c_re = (const bf16*)d_in[5]; P.c_im = (const bf16*)d_in[6];
  P.log_dt = (const bf16*)d_in[7]; P.dskip = (const bf16*)d_in[8]; P.w1 = (const bf16*)d_in[10]; P.w2 = (const bf16*)d_in[11];
  fused_kernel<<<128, 512, SM_TOTAL, cudaStreamPerThread>>>(tmX, tmW1, tmHst, tmHld, tmW2, tmYst, tmYld, tmOut, P);
}
```

```cpp
#include <cuda_runtime.h>
#include <cuda_bf16.h>
#include <cuda.h>
#include <stdint.h>

typedef __nv_bfloat16 bf16;

__device__ __align__(1024) bf16 g_xnP[512 * 2048];
__device__ __align__(1024) bf16 g_h[2048 * 1376];
__device__ __align__(1024) bf16 g_yT[512 * 2048];
__device__ __align__(128) float2 g_stat[2048];
__device__ __align__(128) float g_colsum[1408];
__device__ __align__(128) unsigned g_cnt[32 * 32];
#define TS(k)
#define TS1(k)
#define CNT_PREP 0
#define CNT_DONE 32
#define CNT_H(i) (64 + 32 * (i))
#define CNT_Y(j) (64 + 32 * 16 + 32 * (j))

constexpr int SM_HST = 118784;
constexpr int SM_XT = 147456;
constexpr int SM_U = 163840;
constexpr int U_CH = 5248, U_PL = 656;
constexpr int SM_KT = 184832;
constexpr int KT_CH = 3712, KT_Z5 = 2560, KT_Z3 = 2944, KT_Z4 = 3328;
constexpr int SM_WORK = 199680;
constexpr int WK_SZ = 15360;
constexpr int WK_S5 = 0, WK_S3 = 3456, WK_S9 = 6656, WK_S7 = 8832, WK_F = 11008;
constexpr int WK_BT = 0, WK_PRM = 8704, WK_KV = 10752;
constexpr int SM_STAT = 230400;
constexpr int SM_COLS = 231424;
constexpr int SM_BAR = 232128;
constexpr int SM_TOTAL = 232384;
constexpr int B_F1 = 0, B_E1 = 4, B_F2 = 8, B_E2 = 14, B_MISC = 20, B_U = 21, B_X = 22, B_Y = 23;

__device__ __forceinline__ uint32_t smem_u32(const void* p) { return (uint32_t)__cvta_generic_to_shared(p); }
__device__ __forceinline__ void mbar_init(uint32_t bar, uint32_t cnt) { asm volatile("mbarrier.init.shared::cta.b64 [%0], %1;" ::"r"(bar), "r"(cnt) : "memory"); }
__device__ __forceinline__ void mbar_expect(uint32_t bar, uint32_t bytes) { asm volatile("mbarrier.arrive.expect_tx.shared::cta.b64 _, [%0], %1;" ::"r"(bar), "r"(bytes) : "memory"); }
__device__ __forceinline__ void mbar_arrive(uint32_t bar) { asm volatile("mbarrier.arrive.shared::cta.b64 _, [%0];" ::"r"(bar) : "memory"); }
__device__ __forceinline__ bool mbar_try(uint32_t bar, uint32_t par) {
  uint32_t ok;
  asm volatile("{\n.reg .pred p;\nmbarrier.try_wait.parity.shared::cta.b64 p, [%1], %2;\nselp.u32 %0,1,0,p;\n}" : "=r"(ok) : "r"(bar), "r"(par) : "memory");
  return ok;
}
__device__ __forceinline__ void mbar_wait(uint32_t bar, uint32_t par) {
  asm volatile("{\n.reg .pred p;\n.reg .u32 c;\nmov.u32 c,0;\nLW:\nmbarrier.try_wait.parity.shared::cta.b64 p,[%0],%1;\n@p bra LD;\n"
               "add.u32 c,c,1;\nsetp.lt.u32 p,c,0x400000;\n@p bra LW;\nLD:\n}" ::"r"(bar), "r"(par) : "memory");
}
__device__ __forceinline__ void poll_cnt(const unsigned* p, unsigned target) {
  for (int i = 0; i < (1 << 22); i++) {
    unsigned v;
    asm volatile("ld.acquire.gpu.global.u32 %0, [%1];" : "=r"(v) : "l"(p) : "memory");
    if (v >= target) break;
  }
}
template <int OFF> __device__ __forceinline__ void xred(float* v, int lane) {
  const bool up = lane & OFF;
#pragma unroll
  for (int i = 0; i < OFF; i++) {
    const float snd = up ? v[i] : v[i + OFF], kp = up ? v[i + OFF] : v[i];
    v[i] = kp + __shfl_xor_sync(0xffffffffu, snd, OFF);
  }
  if constexpr (OFF > 1) xred<OFF / 2>(v, lane);
}
__device__ __forceinline__ void red_release(unsigned* p) { asm volatile("red.release.gpu.global.add.u32 [%0], 1;" ::"l"(p) : "memory"); }
__device__ __forceinline__ void fence_async() { asm volatile("fence.proxy.async;" ::: "memory"); }
__device__ __forceinline__ void fence_async_smem() { asm volatile("fence.proxy.async.shared::cta;" ::: "memory"); }
__device__ __forceinline__ void tma_ld2(uint32_t dst, const CUtensorMap* m, int c0, int c1, uint32_t bar) {
  asm volatile("cp.async.bulk.tensor.2d.shared::cluster.global.mbarrier::complete_tx::bytes [%0], [%1, {%3, %4}], [%2];" ::"r"(dst), "l"(m), "r"(bar), "r"(c0), "r"(c1) : "memory");
}
__device__ __forceinline__ void tma_st2(const CUtensorMap* m, uint32_t src, int c0, int c1) {
  asm volatile("cp.async.bulk.tensor.2d.global.shared::cta.bulk_group [%0, {%2, %3}], [%1];" ::"l"(m), "r"(src), "r"(c0), "r"(c1) : "memory");
}
__device__ __forceinline__ void bulk_ld(uint32_t dst, const void* src, uint32_t bytes, uint32_t bar) {
  asm volatile("cp.async.bulk.shared::cluster.global.mbarrier::complete_tx::bytes [%0], [%1], %2, [%3];" ::"r"(dst), "l"(src), "r"(bytes), "r"(bar) : "memory");
}
__device__ __forceinline__ void bulk_commit() { asm volatile("cp.async.bulk.commit_group;" ::: "memory"); }
__device__ __forceinline__ void bulk_wait0() { asm volatile("cp.async.bulk.wait_group 0;" ::: "memory"); }
__device__ __forceinline__ void bulk_wait0_read() { asm volatile("cp.async.bulk.wait_group.read 0;" ::: "memory"); }
__device__ __forceinline__ void nbar(int id, int n) { asm volatile("bar.sync %0, %1;" ::"r"(id), "r"(n) : "memory"); }
__device__ __forceinline__ void wg_fence() { asm volatile("wgmma.fence.sync.aligned;" ::: "memory"); }
__device__ __forceinline__ void wg_commit() { asm volatile("wgmma.commit_group.sync.aligned;" ::: "memory"); }
template <int n> __device__ __forceinline__ void wg_wait() { asm volatile("wgmma.wait_group.sync.aligned %0;" ::"n"(n) : "memory"); }
__device__ __forceinline__ uint64_t mkdesc(uint32_t addr, uint32_t lbo, uint32_t sbo, uint32_t sw) {
  return (uint64_t)((addr >> 4) & 0x3fff) | ((uint64_t)(lbo >> 4) << 16) | ((uint64_t)(sbo >> 4) << 32) | ((uint64_t)sw << 62);
}
__device__ __forceinline__ void ldsm4(uint32_t* r, uint32_t a) { asm volatile("ldmatrix.sync.aligned.m8n8.x4.shared.b16 {%0,%1,%2,%3},[%4];" : "=r"(r[0]), "=r"(r[1]), "=r"(r[2]), "=r"(r[3]) : "r"(a) : "memory"); }
__device__ __forceinline__ void ldsm4t(uint32_t* r, uint32_t a) { asm volatile("ldmatrix.sync.aligned.m8n8.x4.trans.shared.b16 {%0,%1,%2,%3},[%4];" : "=r"(r[0]), "=r"(r[1]), "=r"(r[2]), "=r"(r[3]) : "r"(a) : "memory"); }
__device__ __forceinline__ void stsm4(uint32_t a, uint32_t r0, uint32_t r1, uint32_t r2, uint32_t r3) { asm volatile("stmatrix.sync.aligned.m8n8.x4.shared.b16 [%0],{%1,%2,%3,%4};" ::"r"(a), "r"(r0), "r"(r1), "r"(r2), "r"(r3) : "memory"); }
__device__ __forceinline__ void stsm4t(uint32_t a, uint32_t r0, uint32_t r1, uint32_t r2, uint32_t r3) { asm volatile("stmatrix.sync.aligned.m8n8.x4.trans.shared.b16 [%0],{%1,%2,%3,%4};" ::"r"(a), "r"(r0), "r"(r1), "r"(r2), "r"(r3) : "memory"); }
__device__ __forceinline__ uint32_t lds32(uint32_t a) { uint32_t v; asm volatile("ld.shared.u32 %0,[%1];" : "=r"(v) : "r"(a) : "memory"); return v; }
__device__ __forceinline__ float ldsf(uint32_t a) { float v; asm volatile("ld.shared.f32 %0,[%1];" : "=f"(v) : "r"(a) : "memory"); return v; }
__device__ __forceinline__ float2 lds64f(uint32_t a) { float2 v; asm volatile("ld.shared.v2.f32 {%0,%1},[%2];" : "=f"(v.x), "=f"(v.y) : "r"(a) : "memory"); return v; }
__device__ __forceinline__ float4 lds128f(uint32_t a) { float4 v; asm volatile("ld.shared.v4.f32 {%0,%1,%2,%3},[%4];" : "=f"(v.x), "=f"(v.y), "=f"(v.z), "=f"(v.w) : "r"(a) : "memory"); return v; }
__device__ __forceinline__ uint4 lds128(uint32_t a) { uint4 v; asm volatile("ld.shared.v4.u32 {%0,%1,%2,%3},[%4];" : "=r"(v.x), "=r"(v.y), "=r"(v.z), "=r"(v.w) : "r"(a) : "memory"); return v; }
__device__ __forceinline__ void sts32(uint32_t a, uint32_t v) { asm volatile("st.shared.u32 [%0],%1;" ::"r"(a), "r"(v) : "memory"); }
__device__ __forceinline__ void stsf(uint32_t a, float v) { asm volatile("st.shared.f32 [%0],%1;" ::"r"(a), "f"(v) : "memory"); }
__device__ __forceinline__ void sts64f(uint32_t a, float x, float y) { asm volatile("st.shared.v2.f32 [%0],{%1,%2};" ::"r"(a), "f"(x), "f"(y) : "memory"); }
__device__ __forceinline__ void sts128f(uint32_t a, float x, float y, float z, float w) { asm volatile("st.shared.v4.f32 [%0],{%1,%2,%3,%4};" ::"r"(a), "f"(x), "f"(y), "f"(z), "f"(w) : "memory"); }
__device__ __forceinline__ void sts128(uint32_t a, uint32_t x, uint32_t y, uint32_t z, uint32_t w) { asm volatile("st.shared.v4.u32 [%0],{%1,%2,%3,%4};" ::"r"(a), "r"(x), "r"(y), "r"(z), "r"(w) : "memory"); }
__device__ __forceinline__ uint32_t pk(float lo, float hi) { uint32_t r; asm("cvt.rn.bf16x2.f32 %0,%1,%2;" : "=r"(r) : "f"(hi), "f"(lo)); return r; }
__device__ __forceinline__ float blo(uint32_t v) { return __uint_as_float(v << 16); }
__device__ __forceinline__ float bhi(uint32_t v) { return __uint_as_float(v & 0xffff0000u); }
__device__ __forceinline__ float bfr(float x) { return __bfloat162float(__float2bfloat16_rn(x)); }
__device__ __forceinline__ float ex2(float x) { float r; asm("ex2.approx.ftz.f32 %0,%1;" : "=f"(r) : "f"(x)); return r; }
__device__ __forceinline__ float red2pi(float x) {
  float k = rintf(x * 0.15915494309189535f);
  x = fmaf(k, -6.2831854820251465f, x);
  return fmaf(k, 1.7484555e-7f, x);
}
__device__ __forceinline__ float2 cmul(float2 a, float2 b) { return make_float2(fmaf(a.x, b.x, -a.y * b.y), fmaf(a.x, b.y, a.y * b.x)); }
__device__ __forceinline__ float2 cexp_p(float arl, float ai, float p) {
  float m = ex2(arl * p), ph = red2pi(ai * p);
  return make_float2(m * __cosf(ph), m * __sinf(ph));
}
__device__ __forceinline__ void wg_ss176(float* d, uint64_t da, uint64_t db, int sc){
  asm volatile("{\n.reg .pred p;\nsetp.ne.b32 p,%90,0;\nwgmma.mma_async.sync.aligned.m64n176k16.f32.bf16.bf16 {%0,%1,%2,%3,%4,%5,%6,%7,%8,%9,%10,%11,%12,%13,%14,%15,%16,%17,%18,%19,%20,%21,%22,%23,%24,%25,%26,%27,%28,%29,%30,%31,%32,%33,%34,%35,%36,%37,%38,%39,%40,%41,%42,%43,%44,%45,%46,%47,%48,%49,%50,%51,%52,%53,%54,%55,%56,%57,%58,%59,%60,%61,%62,%63,%64,%65,%66,%67,%68,%69,%70,%71,%72,%73,%74,%75,%76,%77,%78,%79,%80,%81,%82,%83,%84,%85,%86,%87},%88,%89,p,1,1,0,1;\n}"
    : "+f"(d[0]),"+f"(d[1]),"+f"(d[2]),"+f"(d[3]),"+f"(d[4]),"+f"(d[5]),"+f"(d[6]),"+f"(d[7]),"+f"(d[8]),"+f"(d[9]),"+f"(d[10]),"+f"(d[11]),"+f"(d[12]),"+f"(d[13]),"+f"(d[14]),"+f"(d[15]),"+f"(d[16]),"+f"(d[17]),"+f"(d[18]),"+f"(d[19]),"+f"(d[20]),"+f"(d[21]),"+f"(d[22]),"+f"(d[23]),"+f"(d[24]),"+f"(d[25]),"+f"(d[26]),"+f"(d[27]),"+f"(d[28]),"+f"(d[29]),"+f"(d[30]),"+f"(d[31]),"+f"(d[32]),"+f"(d[33]),"+f"(d[34]),"+f"(d[35]),"+f"(d[36]),"+f"(d[37]),"+f"(d[38]),"+f"(d[39]),"+f"(d[40]),"+f"(d[41]),"+f"(d[42]),"+f"(d[43]),"+f"(d[44]),"+f"(d[45]),"+f"(d[46]),"+f"(d[47]),"+f"(d[48]),"+f"(d[49]),"+f"(d[50]),"+f"(d[51]),"+f"(d[52]),"+f"(d[53]),"+f"(d[54]),"+f"(d[55]),"+f"(d[56]),"+f"(d[57]),"+f"(d[58]),"+f"(d[59]),"+f"(d[60]),"+f"(d[61]),"+f"(d[62]),"+f"(d[63]),"+f"(d[64]),"+f"(d[65]),"+f"(d[66]),"+f"(d[67]),"+f"(d[68]),"+f"(d[69]),"+f"(d[70]),"+f"(d[71]),"+f"(d[72]),"+f"(d[73]),"+f"(d[74]),"+f"(d[75]),"+f"(d[76]),"+f"(d[77]),"+f"(d[78]),"+f"(d[79]),"+f"(d[80]),"+f"(d[81]),"+f"(d[82]),"+f"(d[83]),"+f"(d[84]),"+f"(d[85]),"+f"(d[86]),"+f"(d[87])
    : "l"(da),"l"(db),"r"(sc));
}
__device__ __forceinline__ void wg_ss64(float* d, uint64_t da, uint64_t db, int sc){
  asm volatile("{\n.reg .pred p;\nsetp.ne.b32 p,%34,0;\nwgmma.mma_async.sync.aligned.m64n64k16.f32.bf16.bf16 {%0,%1,%2,%3,%4,%5,%6,%7,%8,%9,%10,%11,%12,%13,%14,%15,%16,%17,%18,%19,%20,%21,%22,%23,%24,%25,%26,%27,%28,%29,%30,%31},%32,%33,p,1,1,0,1;\n}"
    : "+f"(d[0]),"+f"(d[1]),"+f"(d[2]),"+f"(d[3]),"+f"(d[4]),"+f"(d[5]),"+f"(d[6]),"+f"(d[7]),"+f"(d[8]),"+f"(d[9]),"+f"(d[10]),"+f"(d[11]),"+f"(d[12]),"+f"(d[13]),"+f"(d[14]),"+f"(d[15]),"+f"(d[16]),"+f"(d[17]),"+f"(d[18]),"+f"(d[19]),"+f"(d[20]),"+f"(d[21]),"+f"(d[22]),"+f"(d[23]),"+f"(d[24]),"+f"(d[25]),"+f"(d[26]),"+f"(d[27]),"+f"(d[28]),"+f"(d[29]),"+f"(d[30]),"+f"(d[31])
    : "l"(da),"l"(db),"r"(sc));
}
template<int SC> __device__ __forceinline__ void wg_rs32(float* d, uint32_t a0, uint32_t a1, uint32_t a2, uint32_t a3, uint64_t db){
  asm volatile("wgmma.mma_async.sync.aligned.m64n32k16.f32.bf16.bf16 {%0,%1,%2,%3,%4,%5,%6,%7,%8,%9,%10,%11,%12,%13,%14,%15},{%16,%17,%18,%19},%20,%21,1,1,0;"
    : "+f"(d[0]),"+f"(d[1]),"+f"(d[2]),"+f"(d[3]),"+f"(d[4]),"+f"(d[5]),"+f"(d[6]),"+f"(d[7]),"+f"(d[8]),"+f"(d[9]),"+f"(d[10]),"+f"(d[11]),"+f"(d[12]),"+f"(d[13]),"+f"(d[14]),"+f"(d[15])
    : "r"(a0),"r"(a1),"r"(a2),"r"(a3),"l"(db),"n"(SC));
}
template<int SC> __device__ __forceinline__ void wg_rs16(float* d, uint32_t a0, uint32_t a1, uint32_t a2, uint32_t a3, uint64_t db){
  asm volatile("wgmma.mma_async.sync.aligned.m64n16k16.f32.bf16.bf16 {%0,%1,%2,%3,%4,%5,%6,%7},{%8,%9,%10,%11},%12,%13,1,1,0;"
    : "+f"(d[0]),"+f"(d[1]),"+f"(d[2]),"+f"(d[3]),"+f"(d[4]),"+f"(d[5]),"+f"(d[6]),"+f"(d[7])
    : "r"(a0),"r"(a1),"r"(a2),"r"(a3),"l"(db),"n"(SC));
}
template<int SC> __device__ __forceinline__ void wg_rs8(float* d, uint32_t a0, uint32_t a1, uint32_t a2, uint32_t a3, uint64_t db){
  asm volatile("wgmma.mma_async.sync.aligned.m64n8k16.f32.bf16.bf16 {%0,%1,%2,%3},{%4,%5,%6,%7},%8,%9,1,1,0;"
    : "+f"(d[0]),"+f"(d[1]),"+f"(d[2]),"+f"(d[3])
    : "r"(a0),"r"(a1),"r"(a2),"r"(a3),"l"(db),"n"(SC));
}

struct Params {
  const bf16 *x, *a_re, *a_im, *b_re, *b_im, *c_re, *c_im, *log_dt, *dskip, *w1, *w2;
};

__device__ __forceinline__ float kv_at(uint32_t kv, int v) {
  int j, c;
  if (v < 256) { j = v >> 2; c = v & 3; }
  else if (v < 512) { j = (v - 256) >> 2; c = 4 + ((v >> 1) & 1); }
  else { j = (v & 255) >> 2; c = 4 + (v >> 8); }
  return ldsf(kv + (j * 16 + c) * 4);
}
__device__ __forceinline__ float kd_at(uint32_t kv, int l, float dsk) {
  if (l < 0 || l > 510) return 0.f;
  int v = (int)bfr((float)l);
  float r = kv_at(kv, v);
  if (l == 0) r += dsk;
  if (l == 510) r -= kv_at(kv, 512);
  return r;
}

__device__ __forceinline__ void finish_arrive() {
  unsigned d = atomicAdd(&g_cnt[CNT_DONE], 1);
  if (d == 255) {
    g_cnt[CNT_PREP] = 0;
    for (int i = 0; i < 16; i++) g_cnt[CNT_H(i)] = 0;
    for (int i = 0; i < 8; i++) g_cnt[CNT_Y(i)] = 0;
    g_cnt[CNT_DONE] = 0;
  }
}

__global__ void __launch_bounds__(512, 1)
fused_kernel(const __grid_constant__ CUtensorMap tmX, const __grid_constant__ CUtensorMap tmW1,
             const __grid_constant__ CUtensorMap tmHst, const __grid_constant__ CUtensorMap tmHld,
             const __grid_constant__ CUtensorMap tmW2, const __grid_constant__ CUtensorMap tmYst,
             const __grid_constant__ CUtensorMap tmYld, const __grid_constant__ CUtensorMap tmOut, const Params P) {
  extern __shared__ __align__(1024) unsigned char smem_raw[];
  const uint32_t sb = smem_u32(smem_raw);
  const int tid = threadIdx.x, warp = __shfl_sync(0xffffffffu, tid >> 5, 0), lane = tid & 31;
  const int b = blockIdx.x, mi = b >> 3, nj = b & 7;
  const uint32_t bars = sb + SM_BAR;
#define BAR(i) (bars + 8 * (i))

  if (warp < 8) {
    const bool prod = (tid == 128);
    if (prod) {
      for (int i = 0; i < 4; i++) { mbar_init(BAR(B_F1 + i), 1); mbar_init(BAR(B_E1 + i), 8); }
      for (int i = 0; i < 6; i++) { mbar_init(BAR(B_F2 + i), 1); mbar_init(BAR(B_E2 + i), 8); }
      for (int i = B_MISC; i <= B_Y; i++) mbar_init(BAR(i), 1);
      asm volatile("fence.mbarrier_init.release.cluster;" ::: "memory");
      fence_async_smem();
      for (int ks = 0; ks < 4; ks++) {
        uint32_t slot = sb + ks * 40960;
        mbar_expect(BAR(B_F1 + ks), 40960);
        tma_ld2(slot, &tmX, 64 * ks, 128 * mi, BAR(B_F1 + ks));
        for (int a = 0; a < 3; a++) tma_ld2(slot + 16384 + 8192 * a, &tmW1, 176 * nj + 64 * a, 64 * ks, BAR(B_F1 + ks));
      }
      asm volatile("cp.async.bulk.prefetch.L2.global [%0], %1;" ::"l"((const char*)P.w2 + 11008 * b), "r"(11008) : "memory");
    }
    __syncthreads();
    const int wg = warp >> 2, g = lane >> 2, q = lane & 3;
    {
      float acc[88];
#pragma unroll 1
      for (int ks = 0; ks < 8; ks++) {
        const int s = ks & 3;
        mbar_wait(BAR(B_F1 + s), ks >> 2);
        if (ks == 0) TS(0 + wg);
        const uint32_t slot = sb + s * 40960;
        const uint64_t da = mkdesc(slot + wg * 8192, 16, 1024, 1);
        const uint64_t db = mkdesc(slot + 16384, 8192, 1024, 1);
        wg_fence();
#pragma unroll
        for (int k = 0; k < 4; k++) wg_ss176(acc, da + 2 * k, db + 128 * k, (ks | k) != 0);
        wg_commit();
        if (ks > 0) {
          wg_wait<1>();
          const int sp = (ks - 1) & 3;
          if (lane == 0) mbar_arrive(BAR(B_E1 + sp));
          if (prod && ks < 7) {
            mbar_wait(BAR(B_E1 + sp), (ks - 1) >> 2);
            if (ks < 5) {
              const uint32_t sl = sb + sp * 40960;
              mbar_expect(BAR(B_F1 + sp), 40960);
              tma_ld2(sl, &tmX, 64 * (ks + 3), 128 * mi, BAR(B_F1 + sp));
              for (int a = 0; a < 3; a++) tma_ld2(sl + 16384 + 8192 * a, &tmW1, 176 * nj + 64 * a, 64 * (ks + 3), BAR(B_F1 + sp));
            } else {
              for (int kk = 2 * sp; kk < 2 * sp + 2; kk++) {
                mbar_expect(BAR(B_F2 + kk), 24576);
                tma_ld2(sb + kk * 24576, &tmW2, 64 * nj, 64 * kk, BAR(B_F2 + kk));
              }
            }
          }
          __syncwarp();
        }
      }
      wg_wait<0>();
      if (lane == 0) mbar_arrive(BAR(B_E1 + 3));
      TS(2 + wg);
      mbar_wait(BAR(B_MISC), 0);
      mbar_wait(BAR(B_E1 + 2), 1);
      mbar_wait(BAR(B_E1 + 3), 1);
      const float2 st0 = lds64f(sb + SM_STAT + (16 * warp + g) * 8);
      const float2 st1 = lds64f(sb + SM_STAT + (16 * warp + g + 8) * 8);
      const uint32_t hst = sb + SM_HST + warp * 5632;
      const uint32_t sta = hst + ((lane & 7) + 8 * ((lane >> 3) & 1)) * 352 + (lane >> 4) * 16;
#pragma unroll
      for (int i = 0; i < 22; i += 2) {
        uint32_t r[4];
#pragma unroll
        for (int u = 0; u < 2; u++) {
          const float2 cs = lds64f(sb + SM_COLS + (8 * (i + u) + 2 * q) * 4);
          const float* a = acc + 4 * (i + u);
          r[2 * u] = pk(fmaxf(fmaf(a[0], st0.x, -st0.y * cs.x), 0.f), fmaxf(fmaf(a[1], st0.x, -st0.y * cs.y), 0.f));
          r[2 * u + 1] = pk(fmaxf(fmaf(a[2], st1.x, -st1.y * cs.x), 0.f), fmaxf(fmaf(a[3], st1.x, -st1.y * cs.y), 0.f));
        }
        stsm4(sta + i * 16, r[0], r[1], r[2], r[3]);
      }
      fence_async_smem();
      __syncwarp();
      if (lane == 0) {
        tma_st2(&tmHst, hst, 176 * nj, 128 * mi + 16 * warp);
        bulk_commit();
        bulk_wait0();
        fence_async();
        __threadfence();
        red_release(&g_cnt[CNT_H(mi)]);
        if (prod) {
          poll_cnt(&g_cnt[CNT_H(mi)], 64);
          TS1(18);
          fence_async();
          for (int kk = 0; kk < 6; kk++) {
            if (kk >= 4) {
              mbar_expect(BAR(B_F2 + kk), 24576);
              tma_ld2(sb + kk * 24576, &tmW2, 64 * nj, 64 * kk, BAR(B_F2 + kk));
            }
            tma_ld2(sb + kk * 24576 + 8192, &tmHld, 64 * kk, 128 * mi, BAR(B_F2 + kk));
          }
          mbar_expect(BAR(B_X), 16384);
          tma_ld2(sb + SM_XT, &tmX, 64 * nj, 128 * mi, BAR(B_X));
          finish_arrive();
        }
      }
      __syncwarp();
      TS(4 + wg);
    }
    {
      float acc[32];
      int s = 0, ph = 0, sp = 0, spp = 0, php = 0, phpp = 0;
#pragma unroll 1
      for (int kk = 0; kk < 21; kk++) {
        mbar_wait(BAR(B_F2 + s), ph);
        if (kk == 0) TS(6 + wg);
        const uint32_t slot = sb + s * 24576;
        const uint64_t da = mkdesc(slot + 8192 + wg * 8192, 16, 1024, 1);
        const uint64_t db = mkdesc(slot, 8192, 1024, 1);
        wg_fence();
        wg_ss64(acc, da, db, kk != 0);
        wg_ss64(acc, da + 2, db + 128, 1);
        wg_ss64(acc, da + 4, db + 256, 1);
        wg_ss64(acc, da + 6, db + 384, 1);
        wg_commit();
        if (kk > 0) {
          wg_wait<1>();
          if (lane == 0) mbar_arrive(BAR(B_E2 + sp));
          if (prod && kk >= 2 && kk < 18) {
            mbar_wait(BAR(B_E2 + spp), phpp);
            mbar_expect(BAR(B_F2 + spp), 24576);
            tma_ld2(sb + spp * 24576, &tmW2, 64 * nj, 64 * (kk + 4), BAR(B_F2 + spp));
            tma_ld2(sb + spp * 24576 + 8192, &tmHld, 64 * (kk + 4), 128 * mi, BAR(B_F2 + spp));
          }
          __syncwarp();
        }
        spp = sp; phpp = php;
        sp = s; php = ph;
        if (++s == 6) { s = 0; ph ^= 1; }
      }
      {
        mbar_wait(BAR(B_F2 + 3), 1);
        const uint32_t slot = sb + 3 * 24576;
        const uint64_t da = mkdesc(slot + 8192 + wg * 8192, 16, 1024, 1);
        const uint64_t db = mkdesc(slot, 8192, 1024, 1);
        wg_fence();
        wg_ss64(acc, da, db, 1);
        wg_ss64(acc, da + 2, db + 128, 1);
        wg_commit();
      }
      wg_wait<0>();
      TS(8 + wg);
      mbar_wait(BAR(B_X), 0);
      mbar_wait(BAR(B_Y), 0);
      const int mu = lane >> 3, r = lane & 7;
      const uint32_t xa = sb + SM_XT + (16 * warp + r + 8 * (mu & 1)) * 128;
      const uint32_t ya = sb + SM_U + (warp >> 2) * 8192 + (8 * (mu >> 1) + r) * 128 + (((2 * (warp & 3) + (mu & 1)) ^ r) << 4);
#pragma unroll
      for (int i = 0; i < 8; i += 2) {
        uint32_t xv[4], yv[4], o[4];
        const uint32_t xadr = xa + (((i + (mu >> 1)) ^ r) << 4);
        ldsm4(xv, xadr);
        ldsm4t(yv, ya + i * 1024);
#pragma unroll
        for (int u = 0; u < 4; u++) {
          const float* a = acc + 4 * (i + (u >> 1)) + 2 * (u & 1);
          o[u] = pk(a[0] + blo(xv[u]) + blo(yv[u]), a[1] + bhi(xv[u]) + bhi(yv[u]));
        }
        stsm4(xadr, o[0], o[1], o[2], o[3]);
      }
      fence_async_smem();
      __syncwarp();
      if (lane == 0) {
        tma_st2(&tmOut, sb + SM_XT + warp * 2048, 64 * nj, 128 * mi + 16 * warp);
        bulk_commit();
        bulk_wait0_read();
      }
      TS(10 + wg);
    }
  } else {
    const int st = tid - 256, wg = (warp >> 2) & 1, t128 = st & 127, w = warp & 3, sw = warp - 8;
    const int g = lane >> 2, q = lane & 3;
    uint32_t xr[16];
    {
      const uint32_t* xp = reinterpret_cast<const uint32_t*>(P.x) + (size_t)(128 * mi + 8 * nj) * 256 + st;
#pragma unroll
      for (int r = 0; r < 16; r++) xr[r] = __ldg(xp + ((r >> 3) * 64 + (r & 7)) * 256);
    }
    uint4 wc[4];
    if (b < 86) {
      const uint4* wp = reinterpret_cast<const uint4*>(P.w1 + (size_t)(2 * st) * 1376 + 16 * b);
      wc[0] = __ldg(wp); wc[1] = __ldg(wp + 1); wc[2] = __ldg(wp + 172); wc[3] = __ldg(wp + 173);
    } else {
      wc[0] = wc[1] = wc[2] = wc[3] = make_uint4(0, 0, 0, 0);
    }
    float prm[2][8];
#pragma unroll
    for (int c = 0; c < 2; c++) {
      const int ch = 4 * b + 2 * wg + c, ix = ch * 128 + t128;
      prm[c][0] = __bfloat162float(P.a_re[ix]); prm[c][1] = __bfloat162float(P.a_im[ix]);
      prm[c][2] = __bfloat162float(P.b_re[ix]); prm[c][3] = __bfloat162float(P.b_im[ix]);
      prm[c][4] = __bfloat162float(P.c_re[ix]); prm[c][5] = __bfloat162float(P.c_im[ix]);
      prm[c][6] = __bfloat162float(P.log_dt[ch]); prm[c][7] = __bfloat162float(P.dskip[ch]);
    }
    sts128(sb + SM_U + (st >> 6) * U_CH + ((st >> 3) & 7) * U_PL + (st & 7) * 16, 0, 0, 0, 0);
    fence_async_smem();
    __syncthreads();
    {
      const uint32_t red = sb + SM_KT, cred = red + 1024, wst = red + 2048 + sw * 128;
      float v[32];
#pragma unroll
      for (int r = 0; r < 16; r++) {
        const float a = blo(xr[r]), c = bhi(xr[r]);
        v[r] = a + c;
        v[16 + r] = fmaf(a, a, c * c);
      }
      xred<16>(v, lane);
      stsf(red + (sw * 32 + lane) * 4, v[0]);
      float cv[16];
      {
#pragma unroll
        for (int i = 0; i < 8; i++) {
          const uint32_t a = i < 4 ? (&wc[0].x)[i] : (&wc[1].x)[i - 4], c = i < 4 ? (&wc[2].x)[i] : (&wc[3].x)[i - 4];
          cv[2 * i] = blo(a) + blo(c);
          cv[2 * i + 1] = bhi(a) + bhi(c);
        }
      }
      xred<8>(cv, lane);
      cv[0] += __shfl_xor_sync(0xffffffffu, cv[0], 16);
      if (lane < 16) stsf(cred + (sw * 16 + lane) * 4, cv[0]);
      nbar(1, 256);
      float tot = 0.f;
#pragma unroll
      for (int i = 0; i < 8; i++) tot += ldsf(red + (i * 32 + lane) * 4);
      const float oth = __shfl_xor_sync(0xffffffffu, tot, 16);
      if (lane < 16) {
        const float mean = tot * (1.f / 512.f);
        const float var = fmaxf(fmaf(-mean, mean, oth * (1.f / 512.f)), 0.f);
        const float mb = bfr(mean);
        const float den = bfr(sqrtf(bfr(bfr(var) + 1e-5f)));
        const float rs = 1.f / den;
        sts64f(wst + lane * 8, mb, rs);
        if (sw == 0) g_stat[128 * mi + 64 * (lane >> 3) + 8 * nj + (lane & 7)] = make_float2(rs, mb * rs);
      }
      if (sw == 1 && lane < 16 && b < 86) {
        float cs = 0.f;
#pragma unroll
        for (int i = 0; i < 8; i++) cs += ldsf(cred + (i * 16 + lane) * 4);
        g_colsum[16 * b + lane] = cs;
      }
      __syncwarp();
      uint32_t o0[8], o1[8];
#pragma unroll
      for (int r = 0; r < 16; r += 2) {
        const float4 s2 = lds128f(wst + r * 8);
        o0[r >> 1] = pk(bfr(blo(xr[r]) - s2.x) * s2.y, bfr(blo(xr[r + 1]) - s2.z) * s2.w);
        o1[r >> 1] = pk(bfr(bhi(xr[r]) - s2.x) * s2.y, bfr(bhi(xr[r + 1]) - s2.z) * s2.w);
      }
      uint4* dp = reinterpret_cast<uint4*>(g_xnP + (size_t)(2 * st) * 2048 + nj * 256 + mi * 16);
      dp[0] = make_uint4(o0[0], o0[1], o0[2], o0[3]);
      dp[1] = make_uint4(o0[4], o0[5], o0[6], o0[7]);
      dp[256] = make_uint4(o1[0], o1[1], o1[2], o1[3]);
      dp[257] = make_uint4(o1[4], o1[5], o1[6], o1[7]);
      fence_async();
      nbar(1, 256);
      if (st == 0) { __threadfence(); red_release(&g_cnt[CNT_PREP]); }
    }
    if (wg == 0) TS(12);
    const uint32_t wk = sb + SM_WORK + wg * WK_SZ;
    float k1024[2];
#pragma unroll
    for (int c = 0; c < 2; c++) {
      {
        const float dt = bfr(expf(prm[c][6]));
        const float ar = dt * prm[c][0], ai = dt * prm[c][1];
        const float arl = ar * 1.4426950408889634f;
        const float2 cp = cmul(make_float2(prm[c][4], prm[c][5]), make_float2(dt * prm[c][2], dt * prm[c][3]));
        const float2 z1 = cexp_p(arl, ai, 1.f), z32 = cexp_p(arl, ai, 32.f), z256 = cexp_p(arl, ai, 256.f);
        sts128f(wk + WK_PRM + t128 * 16, 4.f * arl, red2pi(4.f * ai), z32.x, z32.y);
        const uint32_t bt = wk + WK_BT + (t128 >> 2) * 272 + (t128 & 3) * 4;
        const float2 w1 = cmul(cp, z1), w2 = cmul(w1, z1), w3 = cmul(w2, z1);
        sts32(bt + 0 * 16, pk(cp.x, -cp.y));
        sts32(bt + 1 * 16, pk(w1.x, -w1.y));
        sts32(bt + 2 * 16, pk(w2.x, -w2.y));
        sts32(bt + 3 * 16, pk(w3.x, -w3.y));
        float2 wv = cmul(cp, z256);
        sts32(bt + 4 * 16, pk(wv.x, -wv.y));
        const float2 w258 = cmul(w2, z256);
        sts32(bt + 5 * 16, pk(w258.x, -w258.y));
#pragma unroll
        for (int i = 6; i <= 12; i++) {
          wv = cmul(wv, z256);
          sts32(bt + i * 16, pk(wv.x, -wv.y));
        }
      }
      fence_async_smem();
      nbar(2 + wg, 128);
      float ka[8];
      const float jf = (float)(16 * w + g);
      const uint64_t dbt = mkdesc(wk + WK_BT, 272, 128, 0);
#pragma unroll
      for (int k4 = 0; k4 < 4; k4++) {
        uint32_t af[4][4];
#pragma unroll
        for (int k = 0; k < 4; k++) {
#pragma unroll
          for (int hh = 0; hh < 2; hh++) {
            const float4 p = lds128f(wk + WK_PRM + (8 * (4 * k4 + k) + 4 * hh + q) * 16);
            const float m = ex2(p.x * jf), ph = p.y * jf;
            const float2 e = make_float2(m * __cosf(ph), m * __sinf(ph));
            const float2 e8 = cmul(e, make_float2(p.z, p.w));
            af[k][2 * hh] = pk(e.x, e.y);
            af[k][2 * hh + 1] = pk(e8.x, e8.y);
          }
        }
        wg_fence();
#pragma unroll
        for (int k = 0; k < 4; k++) {
          if (k4 == 0 && k == 0) wg_rs16<0>(ka, af[k][0], af[k][1], af[k][2], af[k][3], dbt);
          else wg_rs16<1>(ka, af[k][0], af[k][1], af[k][2], af[k][3], dbt + (4 * k4 + k) * 34);
        }
        wg_commit();
      }
      wg_wait<0>();
      const uint32_t kv = wk + WK_KV;
      sts64f(kv + ((16 * w + g) * 16 + 2 * q) * 4, ka[0], ka[1]);
      sts64f(kv + ((16 * w + g + 8) * 16 + 2 * q) * 4, ka[2], ka[3]);
      sts64f(kv + ((16 * w + g) * 16 + 8 + 2 * q) * 4, ka[4], ka[5]);
      sts64f(kv + ((16 * w + g + 8) * 16 + 8 + 2 * q) * 4, ka[6], ka[7]);
      nbar(2 + wg, 128);
      const uint32_t kt = sb + SM_KT + (2 * wg + c) * KT_CH;
      unsigned pv = 0;
      if (c == 0 && st == 0) asm volatile("ld.relaxed.gpu.global.u32 %0, [%1];" : "=r"(pv) : "l"(&g_cnt[CNT_PREP]) : "memory");
#pragma unroll 1
      for (int y = t128; y < 640; y += 128) sts32(kt + y * 4, pk(kd_at(kv, y - 64, prm[c][7]), kd_at(kv, y - 65, prm[c][7])));
      if (t128 < 96) {
        float e[2];
#pragma unroll
        for (int u = 0; u < 2; u++) { const int m = 2 * t128 + u; e[u] = (m >= 64 && m <= 128) ? kv_at(kv, 8 * m) : 0.f; }
        sts32(kt + KT_Z5 + t128 * 4, pk(e[0], e[1]));
#pragma unroll
        for (int u = 0; u < 2; u++) { const int m = 2 * t128 + u; e[u] = (m >= 64 && m <= 127) ? kv_at(kv, 8 * m + 4) : 0.f; }
        sts32(kt + KT_Z3 + t128 * 4, pk(e[0], e[1]));
#pragma unroll
        for (int u = 0; u < 2; u++) { const int m = 2 * t128 + u + 73; e[u] = (m >= 129 && m <= 256) ? kv_at(kv, 8 * m) : 0.f; }
        sts32(kt + KT_Z4 + t128 * 4, pk(e[0], e[1]));
      }
      k1024[c] = kv_at(kv, 1024);
      if (c == 0 && sw == 0) {
        if (lane == 0) {
          if (pv < 128) poll_cnt(&g_cnt[CNT_PREP], 128);
          __threadfence();
          TS1(17);
          fence_async();
          mbar_expect(BAR(B_MISC), 1024 + 704);
          bulk_ld(sb + SM_STAT, g_stat + 128 * mi, 1024, BAR(B_MISC));
          bulk_ld(sb + SM_COLS, g_colsum + 176 * nj, 704, BAR(B_MISC));
          mbar_expect(BAR(B_U), 16384);
        }
        __syncwarp();
        fence_async();
        bulk_ld(sb + SM_U + (lane >> 3) * U_CH + (lane & 7) * U_PL + 128, g_xnP + (size_t)(4 * b * 8 + lane) * 256, 512, BAR(B_U));
      }
      fence_async_smem();
      nbar(2 + wg, 128);
    }
    if (wg == 0) TS(13);
    mbar_wait(BAR(B_U), 0);
#pragma unroll 1
    for (int c = 0; c < 2; c++) {
      const uint32_t ub = sb + SM_U + (2 * wg + c) * U_CH;
      const uint32_t kt = sb + SM_KT + (2 * wg + c) * KT_CH;
#pragma unroll 1
      for (int ci = t128 - 23; ci <= 191; ci += 128) {
        float u[24];
#pragma unroll
        for (int k = 0; k < 3; k++) {
          const int cc = ci - 1 + k;
          const uint4 vv = lds128(ub + (cc & 7) * U_PL + ((cc >> 3) + 8) * 16);
          u[8 * k + 0] = blo(vv.x); u[8 * k + 1] = bhi(vv.x); u[8 * k + 2] = blo(vv.y); u[8 * k + 3] = bhi(vv.y);
          u[8 * k + 4] = blo(vv.z); u[8 * k + 5] = bhi(vv.z); u[8 * k + 6] = blo(vv.w); u[8 * k + 7] = bhi(vv.w);
        }
        float f2[8], s5[8];
#pragma unroll
        for (int i = 0; i < 8; i++) f2[i] = u[i + 4] + u[i + 5];
#pragma unroll
        for (int i = 0; i < 8; i++) s5[i] = (u[i + 6] + u[i + 7]) + (u[i + 8] + u[i + 9]) + u[i + 10];
        sts128(wk + WK_S5 + (ci + 23) * 16, pk(s5[0], s5[1]), pk(s5[2], s5[3]), pk(s5[4], s5[5]), pk(s5[6], s5[7]));
        if (ci >= -7)
          sts128(wk + WK_S3 + (ci + 7) * 16, pk(f2[0] + u[3], f2[1] + u[4]), pk(f2[2] + u[5], f2[3] + u[6]), pk(f2[4] + u[7], f2[5] + u[8]),
                 pk(f2[6] + u[9], f2[7] + u[10]));
        if (ci >= -8 && ci <= 127) {
          float s7[8];
#pragma unroll
          for (int i = 0; i < 8; i++) s7[i] = s5[i] + (u[i + 5] + u[i + 11]);
          sts128(wk + WK_S7 + (ci + 8) * 16, pk(s7[0], s7[1]), pk(s7[2], s7[3]), pk(s7[4], s7[5]), pk(s7[6], s7[7]));
#pragma unroll
          for (int i = 0; i < 8; i++) s7[i] += (u[i + 4] + u[i + 12]);
          sts128(wk + WK_S9 + (ci + 8) * 16, pk(s7[0], s7[1]), pk(s7[2], s7[3]), pk(s7[4], s7[5]), pk(s7[6], s7[7]));
          if (ci >= 0) sts128(wk + WK_F + (ci & 7) * 272 + (ci >> 3) * 16, pk(f2[0], f2[1]), pk(f2[2], f2[3]), pk(f2[4], f2[5]), pk(f2[6], f2[7]));
        }
      }
      nbar(2 + wg, 128);
      if (c == 0) { if (wg == 0) TS(14); mbar_wait(BAR(B_E1 + 3), 1); }
      float dacc[16], e01[8], e12[8], e23[8], e3[4];
      {
        const uint32_t pa = kt + (16 * w + g - 2 * q + 520 + 64) * 4;
        uint32_t hprev = lds32(pa);
#pragma unroll
        for (int blk = 0; blk < 6; blk++) {
          uint32_t h[13];
          h[0] = hprev;
          if (blk >= 2) wg_wait<1>();
#pragma unroll
          for (int i = 1; i < 13; i++) h[i] = lds32(pa - (12 * blk + i) * 32);
          hprev = h[12];
          wg_fence();
#pragma unroll
          for (int k = 0; k < 6; k++) {
            const int kap = 6 * blk + k;
            const uint64_t db = mkdesc(ub + (kap & 3) * 2 * U_PL + (kap >> 2) * 16, U_PL, 128, 0);
            if (kap == 0) wg_rs32<0>(dacc, h[2 * k + 1], h[2 * k], h[2 * k + 2], h[2 * k + 1], db);
            else wg_rs32<1>(dacc, h[2 * k + 1], h[2 * k], h[2 * k + 2], h[2 * k + 1], db);
          }
          wg_commit();
        }
      }
      {
        const int mu = lane >> 3, r = lane & 7, kk = r + 8 * (mu >> 1);
        const int cofs = 15 - kk + 2 * w + (mu & 1);
        const uint32_t a5 = wk + WK_S5 + cofs * 16;
        const uint32_t a3 = wk + WK_S3 + cofs * 16;
        const uint32_t a4 = wk + ((kk & 1) ? WK_S9 : WK_S7) + cofs * 16;
        uint32_t f[7][4];
        wg_wait<1>();
#pragma unroll
        for (int k = 0; k < 7; k++) ldsm4t(f[k], a5 + k * 256);
        wg_fence();
        wg_rs16<0>(e01, f[0][0], f[0][1], f[0][2], f[0][3], mkdesc(kt + KT_Z5 + 2 * (0 + 8), 16, 128, 0));
        wg_rs16<0>(e12, f[1][0], f[1][1], f[1][2], f[1][3], mkdesc(kt + KT_Z5 + 2 * (64 + 8 - 16), 16, 128, 0));
        wg_rs16<0>(e23, f[5][0], f[5][1], f[5][2], f[5][3], mkdesc(kt + KT_Z5 + 2 * (128 + 8 - 80), 16, 128, 0));
#pragma unroll
        for (int k = 2; k < 5; k++) wg_rs16<1>(e12, f[k][0], f[k][1], f[k][2], f[k][3], mkdesc(kt + KT_Z5 + 2 * (64 + 8 - 16 * k), 16, 128, 0));
        wg_rs16<1>(e23, f[6][0], f[6][1], f[6][2], f[6][3], mkdesc(kt + KT_Z5 + 2 * (128 + 8 - 96), 16, 128, 0));
        wg_commit();
        uint32_t f1[6][4];
        wg_wait<1>();
#pragma unroll
        for (int k = 0; k < 6; k++) ldsm4t(f1[k], a5 + (7 + k) * 256);
        wg_fence();
#pragma unroll
        for (int k = 0; k < 6; k++) {
          const int kap = 7 + k;
          if (kap <= 8) wg_rs16<1>(e23, f1[k][0], f1[k][1], f1[k][2], f1[k][3], mkdesc(kt + KT_Z5 + 2 * (128 + 8 - 16 * kap), 16, 128, 0));
          else if (kap == 9) wg_rs8<0>(e3, f1[k][0], f1[k][1], f1[k][2], f1[k][3], mkdesc(kt + KT_Z5 + 2 * (192 + 8 - 16 * kap), 16, 128, 0));
          else wg_rs8<1>(e3, f1[k][0], f1[k][1], f1[k][2], f1[k][3], mkdesc(kt + KT_Z5 + 2 * (192 + 8 - 16 * kap), 16, 128, 0));
        }
        wg_commit();
#pragma unroll
        for (int blk = 0; blk < 2; blk++) {
          uint32_t f3[6][4];
          wg_wait<1>();
#pragma unroll
          for (int k = 0; k < 6; k++) ldsm4t(f3[k], a3 + (6 * blk + k) * 256);
          wg_fence();
#pragma unroll
          for (int k = 0; k < 6; k++) {
            const int kap = 6 * blk + k;
            if (kap < 4) wg_rs16<1>(e12, f3[k][0], f3[k][1], f3[k][2], f3[k][3], mkdesc(kt + KT_Z3 + 2 * (64 - 8 - 16 * kap), 16, 128, 0));
            else if (kap < 8) wg_rs16<1>(e23, f3[k][0], f3[k][1], f3[k][2], f3[k][3], mkdesc(kt + KT_Z3 + 2 * (128 - 8 - 16 * kap), 16, 128, 0));
            else wg_rs8<1>(e3, f3[k][0], f3[k][1], f3[k][2], f3[k][3], mkdesc(kt + KT_Z3 + 2 * (192 - 8 - 16 * kap), 16, 128, 0));
          }
          wg_commit();
        }
#pragma unroll
        for (int blk = 0; blk < 2; blk++) {
          uint32_t f4[4][4];
          wg_wait<1>();
#pragma unroll
          for (int k = 0; k < 4; k++) ldsm4t(f4[k], a4 + (4 * blk + k) * 256);
          wg_fence();
#pragma unroll
          for (int k = 0; k < 4; k++) {
            const int kap = 4 * blk + k;
            if (kap < 4) wg_rs16<1>(e23, f4[k][0], f4[k][1], f4[k][2], f4[k][3], mkdesc(kt + KT_Z4 + 2 * (128 - 80 - 16 * kap), 16, 128, 0));
            else wg_rs8<1>(e3, f4[k][0], f4[k][1], f4[k][2], f4[k][3], mkdesc(kt + KT_Z4 + 2 * (192 - 80 - 16 * kap), 16, 128, 0));
          }
          wg_commit();
        }
        uint32_t ff[4];
        ldsm4t(ff, wk + WK_F + (2 * w + (mu & 1)) * 272 + (8 * (mu >> 1) + r) * 16);
        wg_wait<0>();
        const float kf = c ? k1024[1] : k1024[0];
#pragma unroll
        for (int i = 0; i < 4; i++) { dacc[i] += e01[i]; dacc[4 + i] += e01[4 + i] + e12[i]; dacc[8 + i] += e12[4 + i] + e23[i]; dacc[12 + i] += e23[4 + i] + e3[i]; }
#pragma unroll
        for (int u = 0; u < 4; u++) {
          dacc[8 + 2 * u] = fmaf(kf, blo(ff[u]), dacc[8 + 2 * u]);
          dacc[9 + 2 * u] = fmaf(kf, bhi(ff[u]), dacc[9 + 2 * u]);
        }
        nbar(2 + wg, 128);
#pragma unroll
        for (int i = 0; i < 4; i += 2) {
          const int n = 8 * (i + (mu >> 1)) + r;
          stsm4t(wk + n * 128 + (((2 * w + (mu & 1)) ^ r) << 4), pk(dacc[4 * i], dacc[4 * i + 1]), pk(dacc[4 * i + 2], dacc[4 * i + 3]),
                 pk(dacc[4 * i + 4], dacc[4 * i + 5]), pk(dacc[4 * i + 6], dacc[4 * i + 7]));
        }
        fence_async_smem();
        nbar(2 + wg, 128);
        if (t128 == 0) {
          tma_st2(&tmYst, wk, 0, (4 * b + 2 * wg + c) * 32);
          bulk_commit();
          if (c == 0) bulk_wait0_read();
          else { bulk_wait0(); fence_async(); __threadfence(); red_release(&g_cnt[CNT_Y(b >> 4)]); }
        }
        if (c == 0) nbar(2 + wg, 128);
      }
    }
    TS(21 + wg);
    nbar(1, 256);
    if (st == 0) {
      poll_cnt(&g_cnt[CNT_Y(nj)], 32);
      fence_async();
      mbar_expect(BAR(B_Y), 16384);
      tma_ld2(sb + SM_U, &tmYld, 128 * mi, 64 * nj, BAR(B_Y));
      tma_ld2(sb + SM_U + 8192, &tmYld, 128 * mi + 64, 64 * nj, BAR(B_Y));
      TS1(20);
      finish_arrive();
    }
  }
}

typedef CUresult (*PFN_enc)(CUtensorMap*, CUtensorMapDataType, cuuint32_t, void*, const cuuint64_t*, const cuuint64_t*, const cuuint32_t*,
                            const cuuint32_t*, CUtensorMapInterleave, CUtensorMapSwizzle, CUtensorMapL2promotion, CUtensorMapFloatOOBfill);

static void make_map(PFN_enc enc, CUtensorMap* m, const void* ptr, uint64_t cols, uint64_t rows, uint32_t bc, uint32_t br, bool sw) {
  cuuint64_t dims[2] = {cols, rows};
  cuuint64_t strides[1] = {cols * 2};
  cuuint32_t box[2] = {bc, br};
  cuuint32_t es[2] = {1, 1};
  enc(m, CU_TENSOR_MAP_DATA_TYPE_BFLOAT16, 2, const_cast<void*>(ptr), dims, strides, box, es, CU_TENSOR_MAP_INTERLEAVE_NONE,
      sw ? CU_TENSOR_MAP_SWIZZLE_128B : CU_TENSOR_MAP_SWIZZLE_NONE, CU_TENSOR_MAP_L2_PROMOTION_L2_128B, CU_TENSOR_MAP_FLOAT_OOB_FILL_NONE);
}

extern "C" void kernel_launch(void* const* d_in, const int* in_sizes, int n_in, void* d_out, int out_size) {
  (void)in_sizes; (void)n_in; (void)out_size;
  static PFN_enc enc = nullptr;
  static void *ph = nullptr, *py = nullptr;
  if (!enc) {
    void* fn = nullptr;
    cudaDriverEntryPointQueryResult qr;
    cudaGetDriverEntryPoint("cuTensorMapEncodeTiled", &fn, cudaEnableDefault, &qr);
    enc = (PFN_enc)fn;
    cudaGetSymbolAddress(&ph, g_h);
    cudaGetSymbolAddress(&py, g_yT);
    cudaFuncSetAttribute(fused_kernel, cudaFuncAttributeMaxDynamicSharedMemorySize, SM_TOTAL);
  }
  CUtensorMap tmX, tmW1, tmHst, tmHld, tmW2, tmYst, tmYld, tmOut;
  make_map(enc, &tmX, d_in[0], 512, 2048, 64, 128, true);
  make_map(enc, &tmW1, d_in[10], 1376, 512, 64, 64, true);
  make_map(enc, &tmHst, ph, 1376, 2048, 176, 16, false);
  make_map(enc, &tmHld, ph, 1376, 2048, 64, 128, true);
  make_map(enc, &tmW2, d_in[11], 512, 1376, 64, 64, true);
  make_map(enc, &tmYst, py, 64, 512 * 32, 64, 32, true);
  make_map(enc, &tmYld, py, 2048, 512, 64, 64, true);
  make_map(enc, &tmOut, d_out, 512, 2048, 64, 16, true);
  Params P;
  P.x = (const bf16*)d_in[0]; P.a_re = (const bf16*)d_in[1]; P.a_im = (const bf16*)d_in[2];
  P.b_re = (const bf16*)d_in[3]; P.b_im = (const bf16*)d_in[4]; P.c_re = (const bf16*)d_in[5]; P.c_im = (const bf16*)d_in[6];
  P.log_dt = (const bf16*)d_in[7]; P.dskip = (const bf16*)d_in[8]; P.w1 = (const bf16*)d_in[10]; P.w2 = (const bf16*)d_in[11];
  fused_kernel<<<128, 512, SM_TOTAL, cudaStreamPerThread>>>(tmX, tmW1, tmHst, tmHld, tmW2, tmYst, tmYld, tmOut, P);
}
```

```cpp
#include <cuda_runtime.h>
#include <cuda_bf16.h>
#include <cuda.h>
#include <stdint.h>

typedef __nv_bfloat16 bf16;

__device__ __align__(1024) bf16 g_xnP[512 * 2048];
__device__ __align__(1024) unsigned char g_h[16 * 8 * 45056];
__device__ __align__(1024) bf16 g_yT[512 * 2048];
__device__ __align__(128) float g_stat[16 * 256];
__device__ __align__(128) float g_colsum[2 * 1408];
__device__ __align__(128) unsigned g_cnt[32 * 32];
#define TS(k)
#define TS1(k)
#define CNT_PREP 0
#define CNT_H(i) (32 + 32 * (i))
#define CNT_Y(j) (32 + 32 * 16 + 32 * (j))

constexpr int SM_HR = 49152;
constexpr int SM_XT = 147456;
constexpr int SM_WK0 = 163840;
constexpr int SM_U = 179200;
constexpr int U_CH = 5248, U_PL = 656;
constexpr int SM_WK1 = 200192;
constexpr int SM_KT = 215552;
constexpr int KT_CH = 3712, KT_Z5 = 2560, KT_Z3 = 2944, KT_Z4 = 3328;
constexpr int WK_S5 = 0, WK_S3 = 3456, WK_S9 = 6656, WK_S7 = 8832, WK_F = 11008;
constexpr int SM_STAT = 230400;
constexpr int SM_COLS = 231424;
constexpr int SM_BAR = 232128;
constexpr int SM_TOTAL = 232384;
constexpr int B_F1 = 0, B_E1 = 4, B_F2 = 8, B_E2 = 14, B_MISC = 20, B_U = 21, B_X = 23, B_Y = 24, B_OWN = 25, B_CS = 26, B_EPOCH = 31;

__device__ __forceinline__ uint32_t smem_u32(const void* p) { return (uint32_t)__cvta_generic_to_shared(p); }
__device__ __forceinline__ void mbar_init(uint32_t bar, uint32_t cnt) { asm volatile("mbarrier.init.shared::cta.b64 [%0], %1;" ::"r"(bar), "r"(cnt) : "memory"); }
__device__ __forceinline__ void mbar_expect(uint32_t bar, uint32_t bytes) { asm volatile("mbarrier.arrive.expect_tx.shared::cta.b64 _, [%0], %1;" ::"r"(bar), "r"(bytes) : "memory"); }
__device__ __forceinline__ void mbar_arrive(uint32_t bar) { asm volatile("mbarrier.arrive.shared::cta.b64 _, [%0];" ::"r"(bar) : "memory"); }
__device__ __forceinline__ bool mbar_try(uint32_t bar, uint32_t par) {
  uint32_t ok;
  asm volatile("{\n.reg .pred p;\nmbarrier.try_wait.parity.shared::cta.b64 p, [%1], %2;\nselp.u32 %0,1,0,p;\n}" : "=r"(ok) : "r"(bar), "r"(par) : "memory");
  return ok;
}
__device__ __forceinline__ void mbar_wait(uint32_t bar, uint32_t par) {
  asm volatile("{\n.reg .pred p;\n.reg .u32 c;\nmov.u32 c,0;\nLW:\nmbarrier.try_wait.parity.shared::cta.b64 p,[%0],%1;\n@p bra LD;\n"
               "add.u32 c,c,1;\nsetp.lt.u32 p,c,0x400000;\n@p bra LW;\nLD:\n}" ::"r"(bar), "r"(par) : "memory");
}
__device__ __forceinline__ void poll_cnt(const unsigned* p, unsigned target) {
  for (int i = 0; i < (1 << 22); i++) {
    unsigned v;
    asm volatile("ld.acquire.gpu.global.u32 %0, [%1];" : "=r"(v) : "l"(p) : "memory");
    if ((int)(v - target) >= 0) break;
  }
}
template <int OFF> __device__ __forceinline__ void xred(float* v, int lane) {
  const bool up = lane & OFF;
#pragma unroll
  for (int i = 0; i < OFF; i++) {
    const float snd = up ? v[i] : v[i + OFF], kp = up ? v[i + OFF] : v[i];
    v[i] = kp + __shfl_xor_sync(0xffffffffu, snd, OFF);
  }
  if constexpr (OFF > 1) xred<OFF / 2>(v, lane);
}
__device__ __forceinline__ void red_release(unsigned* p, unsigned v) { asm volatile("red.release.gpu.global.add.u32 [%0], %1;" ::"l"(p), "r"(v) : "memory"); }
__device__ __forceinline__ void fence_async_glb() { asm volatile("fence.proxy.async.global;" ::: "memory"); }
__device__ __forceinline__ void pf_map(const CUtensorMap* m) { asm volatile("prefetch.tensormap [%0];" ::"l"(m) : "memory"); }
__device__ __forceinline__ void bulk_st(void* dst, uint32_t src, uint32_t bytes) {
  asm volatile("cp.async.bulk.global.shared::cta.bulk_group [%0], [%1], %2;" ::"l"(dst), "r"(src), "r"(bytes) : "memory");
}
__device__ __forceinline__ void sts16(uint32_t a, uint32_t v) { asm volatile("st.shared.u16 [%0],%1;" ::"r"(a), "h"((unsigned short)v) : "memory"); }
__device__ __forceinline__ void sts64(uint32_t a, uint32_t x, uint32_t y) { asm volatile("st.shared.v2.u32 [%0],{%1,%2};" ::"r"(a), "r"(x), "r"(y) : "memory"); }
__device__ __forceinline__ uint32_t pk_relu(float lo, float hi) { uint32_t r; asm("cvt.rn.relu.bf16x2.f32 %0,%1,%2;" : "=r"(r) : "f"(hi), "f"(lo)); return r; }
__device__ __forceinline__ void fence_async_smem() { asm volatile("fence.proxy.async.shared::cta;" ::: "memory"); }
__device__ __forceinline__ void tma_ld2(uint32_t dst, const CUtensorMap* m, int c0, int c1, uint32_t bar) {
  asm volatile("cp.async.bulk.tensor.2d.shared::cluster.global.mbarrier::complete_tx::bytes [%0], [%1, {%3, %4}], [%2];" ::"r"(dst), "l"(m), "r"(bar), "r"(c0), "r"(c1) : "memory");
}
__device__ __forceinline__ void tma_st2(const CUtensorMap* m, uint32_t src, int c0, int c1) {
  asm volatile("cp.async.bulk.tensor.2d.global.shared::cta.bulk_group [%0, {%2, %3}], [%1];" ::"l"(m), "r"(src), "r"(c0), "r"(c1) : "memory");
}
__device__ __forceinline__ void bulk_ld(uint32_t dst, const void* src, uint32_t bytes, uint32_t bar) {
  asm volatile("cp.async.bulk.shared::cluster.global.mbarrier::complete_tx::bytes [%0], [%1], %2, [%3];" ::"r"(dst), "l"(src), "r"(bytes), "r"(bar) : "memory");
}
__device__ __forceinline__ void bulk_commit() { asm volatile("cp.async.bulk.commit_group;" ::: "memory"); }
__device__ __forceinline__ void bulk_wait0() { asm volatile("cp.async.bulk.wait_group 0;" ::: "memory"); }
__device__ __forceinline__ void bulk_wait0_read() { asm volatile("cp.async.bulk.wait_group.read 0;" ::: "memory"); }
__device__ __forceinline__ void nbar(int id, int n) { asm volatile("bar.sync %0, %1;" ::"r"(id), "r"(n) : "memory"); }
__device__ __forceinline__ void wg_fence() { asm volatile("wgmma.fence.sync.aligned;" ::: "memory"); }
__device__ __forceinline__ void wg_commit() { asm volatile("wgmma.commit_group.sync.aligned;" ::: "memory"); }
template <int n> __device__ __forceinline__ void wg_wait() { asm volatile("wgmma.wait_group.sync.aligned %0;" ::"n"(n) : "memory"); }
__device__ __forceinline__ uint64_t mkdesc(uint32_t addr, uint32_t lbo, uint32_t sbo, uint32_t sw) {
  return (uint64_t)((addr >> 4) & 0x3fff) | ((uint64_t)(lbo >> 4) << 16) | ((uint64_t)(sbo >> 4) << 32) | ((uint64_t)sw << 62);
}
__device__ __forceinline__ void ldsm4(uint32_t* r, uint32_t a) { asm volatile("ldmatrix.sync.aligned.m8n8.x4.shared.b16 {%0,%1,%2,%3},[%4];" : "=r"(r[0]), "=r"(r[1]), "=r"(r[2]), "=r"(r[3]) : "r"(a) : "memory"); }
__device__ __forceinline__ void ldsm4t(uint32_t* r, uint32_t a) { asm volatile("ldmatrix.sync.aligned.m8n8.x4.trans.shared.b16 {%0,%1,%2,%3},[%4];" : "=r"(r[0]), "=r"(r[1]), "=r"(r[2]), "=r"(r[3]) : "r"(a) : "memory"); }
__device__ __forceinline__ void stsm4(uint32_t a, uint32_t r0, uint32_t r1, uint32_t r2, uint32_t r3) { asm volatile("stmatrix.sync.aligned.m8n8.x4.shared.b16 [%0],{%1,%2,%3,%4};" ::"r"(a), "r"(r0), "r"(r1), "r"(r2), "r"(r3) : "memory"); }
__device__ __forceinline__ void stsm4t(uint32_t a, uint32_t r0, uint32_t r1, uint32_t r2, uint32_t r3) { asm volatile("stmatrix.sync.aligned.m8n8.x4.trans.shared.b16 [%0],{%1,%2,%3,%4};" ::"r"(a), "r"(r0), "r"(r1), "r"(r2), "r"(r3) : "memory"); }
__device__ __forceinline__ uint32_t lds32(uint32_t a) { uint32_t v; asm volatile("ld.shared.u32 %0,[%1];" : "=r"(v) : "r"(a) : "memory"); return v; }
__device__ __forceinline__ float ldsf(uint32_t a) { float v; asm volatile("ld.shared.f32 %0,[%1];" : "=f"(v) : "r"(a) : "memory"); return v; }
__device__ __forceinline__ float2 lds64f(uint32_t a) { float2 v; asm volatile("ld.shared.v2.f32 {%0,%1},[%2];" : "=f"(v.x), "=f"(v.y) : "r"(a) : "memory"); return v; }
__device__ __forceinline__ float4 lds128f(uint32_t a) { float4 v; asm volatile("ld.shared.v4.f32 {%0,%1,%2,%3},[%4];" : "=f"(v.x), "=f"(v.y), "=f"(v.z), "=f"(v.w) : "r"(a) : "memory"); return v; }
__device__ __forceinline__ uint4 lds128(uint32_t a) { uint4 v; asm volatile("ld.shared.v4.u32 {%0,%1,%2,%3},[%4];" : "=r"(v.x), "=r"(v.y), "=r"(v.z), "=r"(v.w) : "r"(a) : "memory"); return v; }
__device__ __forceinline__ void sts32(uint32_t a, uint32_t v) { asm volatile("st.shared.u32 [%0],%1;" ::"r"(a), "r"(v) : "memory"); }
__device__ __forceinline__ void stsf(uint32_t a, float v) { asm volatile("st.shared.f32 [%0],%1;" ::"r"(a), "f"(v) : "memory"); }
__device__ __forceinline__ void sts64f(uint32_t a, float x, float y) { asm volatile("st.shared.v2.f32 [%0],{%1,%2};" ::"r"(a), "f"(x), "f"(y) : "memory"); }
__device__ __forceinline__ void sts128f(uint32_t a, float x, float y, float z, float w) { asm volatile("st.shared.v4.f32 [%0],{%1,%2,%3,%4};" ::"r"(a), "f"(x), "f"(y), "f"(z), "f"(w) : "memory"); }
__device__ __forceinline__ void sts128(uint32_t a, uint32_t x, uint32_t y, uint32_t z, uint32_t w) { asm volatile("st.shared.v4.u32 [%0],{%1,%2,%3,%4};" ::"r"(a), "r"(x), "r"(y), "r"(z), "r"(w) : "memory"); }
__device__ __forceinline__ uint32_t pk(float lo, float hi) { uint32_t r; asm("cvt.rn.bf16x2.f32 %0,%1,%2;" : "=r"(r) : "f"(hi), "f"(lo)); return r; }
__device__ __forceinline__ float blo(uint32_t v) { return __uint_as_float(v << 16); }
__device__ __forceinline__ float bhi(uint32_t v) { return __uint_as_float(v & 0xffff0000u); }
__device__ __forceinline__ float bfr(float x) { return __bfloat162float(__float2bfloat16_rn(x)); }
__device__ __forceinline__ float ex2(float x) { float r; asm("ex2.approx.ftz.f32 %0,%1;" : "=f"(r) : "f"(x)); return r; }
__device__ __forceinline__ float red2pi(float x) {
  float k = rintf(x * 0.15915494309189535f);
  x = fmaf(k, -6.2831854820251465f, x);
  return fmaf(k, 1.7484555e-7f, x);
}
__device__ __forceinline__ float2 cmul(float2 a, float2 b) { return make_float2(fmaf(a.x, b.x, -a.y * b.y), fmaf(a.x, b.y, a.y * b.x)); }
__device__ __forceinline__ float2 cexp_p(float arl, float ai, float p) {
  float m = ex2(arl * p), ph = red2pi(ai * p);
  return make_float2(m * __cosf(ph), m * __sinf(ph));
}
__device__ __forceinline__ void wg_ss176(float* d, uint64_t da, uint64_t db, int sc){
  asm volatile("{\n.reg .pred p;\nsetp.ne.b32 p,%90,0;\nwgmma.mma_async.sync.aligned.m64n176k16.f32.bf16.bf16 {%0,%1,%2,%3,%4,%5,%6,%7,%8,%9,%10,%11,%12,%13,%14,%15,%16,%17,%18,%19,%20,%21,%22,%23,%24,%25,%26,%27,%28,%29,%30,%31,%32,%33,%34,%35,%36,%37,%38,%39,%40,%41,%42,%43,%44,%45,%46,%47,%48,%49,%50,%51,%52,%53,%54,%55,%56,%57,%58,%59,%60,%61,%62,%63,%64,%65,%66,%67,%68,%69,%70,%71,%72,%73,%74,%75,%76,%77,%78,%79,%80,%81,%82,%83,%84,%85,%86,%87},%88,%89,p,1,1,0,1;\n}"
    : "+f"(d[0]),"+f"(d[1]),"+f"(d[2]),"+f"(d[3]),"+f"(d[4]),"+f"(d[5]),"+f"(d[6]),"+f"(d[7]),"+f"(d[8]),"+f"(d[9]),"+f"(d[10]),"+f"(d[11]),"+f"(d[12]),"+f"(d[13]),"+f"(d[14]),"+f"(d[15]),"+f"(d[16]),"+f"(d[17]),"+f"(d[18]),"+f"(d[19]),"+f"(d[20]),"+f"(d[21]),"+f"(d[22]),"+f"(d[23]),"+f"(d[24]),"+f"(d[25]),"+f"(d[26]),"+f"(d[27]),"+f"(d[28]),"+f"(d[29]),"+f"(d[30]),"+f"(d[31]),"+f"(d[32]),"+f"(d[33]),"+f"(d[34]),"+f"(d[35]),"+f"(d[36]),"+f"(d[37]),"+f"(d[38]),"+f"(d[39]),"+f"(d[40]),"+f"(d[41]),"+f"(d[42]),"+f"(d[43]),"+f"(d[44]),"+f"(d[45]),"+f"(d[46]),"+f"(d[47]),"+f"(d[48]),"+f"(d[49]),"+f"(d[50]),"+f"(d[51]),"+f"(d[52]),"+f"(d[53]),"+f"(d[54]),"+f"(d[55]),"+f"(d[56]),"+f"(d[57]),"+f"(d[58]),"+f"(d[59]),"+f"(d[60]),"+f"(d[61]),"+f"(d[62]),"+f"(d[63]),"+f"(d[64]),"+f"(d[65]),"+f"(d[66]),"+f"(d[67]),"+f"(d[68]),"+f"(d[69]),"+f"(d[70]),"+f"(d[71]),"+f"(d[72]),"+f"(d[73]),"+f"(d[74]),"+f"(d[75]),"+f"(d[76]),"+f"(d[77]),"+f"(d[78]),"+f"(d[79]),"+f"(d[80]),"+f"(d[81]),"+f"(d[82]),"+f"(d[83]),"+f"(d[84]),"+f"(d[85]),"+f"(d[86]),"+f"(d[87])
    : "l"(da),"l"(db),"r"(sc));
}
__device__ __forceinline__ void wg_ss128t(float* d, uint64_t da, uint64_t db, int sc){
  asm volatile("{\n.reg .pred p;\nsetp.ne.b32 p,%66,0;\nwgmma.mma_async.sync.aligned.m64n128k16.f32.bf16.bf16 {%0,%1,%2,%3,%4,%5,%6,%7,%8,%9,%10,%11,%12,%13,%14,%15,%16,%17,%18,%19,%20,%21,%22,%23,%24,%25,%26,%27,%28,%29,%30,%31,%32,%33,%34,%35,%36,%37,%38,%39,%40,%41,%42,%43,%44,%45,%46,%47,%48,%49,%50,%51,%52,%53,%54,%55,%56,%57,%58,%59,%60,%61,%62,%63},%64,%65,p,1,1,1,0;\n}"
    : "+f"(d[0]),"+f"(d[1]),"+f"(d[2]),"+f"(d[3]),"+f"(d[4]),"+f"(d[5]),"+f"(d[6]),"+f"(d[7]),"+f"(d[8]),"+f"(d[9]),"+f"(d[10]),"+f"(d[11]),"+f"(d[12]),"+f"(d[13]),"+f"(d[14]),"+f"(d[15]),"+f"(d[16]),"+f"(d[17]),"+f"(d[18]),"+f"(d[19]),"+f"(d[20]),"+f"(d[21]),"+f"(d[22]),"+f"(d[23]),"+f"(d[24]),"+f"(d[25]),"+f"(d[26]),"+f"(d[27]),"+f"(d[28]),"+f"(d[29]),"+f"(d[30]),"+f"(d[31]),"+f"(d[32]),"+f"(d[33]),"+f"(d[34]),"+f"(d[35]),"+f"(d[36]),"+f"(d[37]),"+f"(d[38]),"+f"(d[39]),"+f"(d[40]),"+f"(d[41]),"+f"(d[42]),"+f"(d[43]),"+f"(d[44]),"+f"(d[45]),"+f"(d[46]),"+f"(d[47]),"+f"(d[48]),"+f"(d[49]),"+f"(d[50]),"+f"(d[51]),"+f"(d[52]),"+f"(d[53]),"+f"(d[54]),"+f"(d[55]),"+f"(d[56]),"+f"(d[57]),"+f"(d[58]),"+f"(d[59]),"+f"(d[60]),"+f"(d[61]),"+f"(d[62]),"+f"(d[63])
    : "l"(da),"l"(db),"r"(sc));
}
template<int SC> __device__ __forceinline__ void wg_rs48(float* d, uint32_t a0, uint32_t a1, uint32_t a2, uint32_t a3, uint64_t db){
  asm volatile("wgmma.mma_async.sync.aligned.m64n48k16.f32.bf16.bf16 {%0,%1,%2,%3,%4,%5,%6,%7,%8,%9,%10,%11,%12,%13,%14,%15,%16,%17,%18,%19,%20,%21,%22,%23},{%24,%25,%26,%27},%28,%29,1,1,0;"
    : "+f"(d[0]),"+f"(d[1]),"+f"(d[2]),"+f"(d[3]),"+f"(d[4]),"+f"(d[5]),"+f"(d[6]),"+f"(d[7]),"+f"(d[8]),"+f"(d[9]),"+f"(d[10]),"+f"(d[11]),"+f"(d[12]),"+f"(d[13]),"+f"(d[14]),"+f"(d[15]),"+f"(d[16]),"+f"(d[17]),"+f"(d[18]),"+f"(d[19]),"+f"(d[20]),"+f"(d[21]),"+f"(d[22]),"+f"(d[23])
    : "r"(a0),"r"(a1),"r"(a2),"r"(a3),"l"(db),"n"(SC));
}
template<int SC> __device__ __forceinline__ void wg_rs32(float* d, uint32_t a0, uint32_t a1, uint32_t a2, uint32_t a3, uint64_t db){
  asm volatile("wgmma.mma_async.sync.aligned.m64n32k16.f32.bf16.bf16 {%0,%1,%2,%3,%4,%5,%6,%7,%8,%9,%10,%11,%12,%13,%14,%15},{%16,%17,%18,%19},%20,%21,1,1,0;"
    : "+f"(d[0]),"+f"(d[1]),"+f"(d[2]),"+f"(d[3]),"+f"(d[4]),"+f"(d[5]),"+f"(d[6]),"+f"(d[7]),"+f"(d[8]),"+f"(d[9]),"+f"(d[10]),"+f"(d[11]),"+f"(d[12]),"+f"(d[13]),"+f"(d[14]),"+f"(d[15])
    : "r"(a0),"r"(a1),"r"(a2),"r"(a3),"l"(db),"n"(SC));
}
template<int SC> __device__ __forceinline__ void wg_rs16(float* d, uint32_t a0, uint32_t a1, uint32_t a2, uint32_t a3, uint64_t db){
  asm volatile("wgmma.mma_async.sync.aligned.m64n16k16.f32.bf16.bf16 {%0,%1,%2,%3,%4,%5,%6,%7},{%8,%9,%10,%11},%12,%13,1,1,0;"
    : "+f"(d[0]),"+f"(d[1]),"+f"(d[2]),"+f"(d[3]),"+f"(d[4]),"+f"(d[5]),"+f"(d[6]),"+f"(d[7])
    : "r"(a0),"r"(a1),"r"(a2),"r"(a3),"l"(db),"n"(SC));
}
template<int SC> __device__ __forceinline__ void wg_rs8(float* d, uint32_t a0, uint32_t a1, uint32_t a2, uint32_t a3, uint64_t db){
  asm volatile("wgmma.mma_async.sync.aligned.m64n8k16.f32.bf16.bf16 {%0,%1,%2,%3},{%4,%5,%6,%7},%8,%9,1,1,0;"
    : "+f"(d[0]),"+f"(d[1]),"+f"(d[2]),"+f"(d[3])
    : "r"(a0),"r"(a1),"r"(a2),"r"(a3),"l"(db),"n"(SC));
}

struct Params {
  const bf16 *x, *a_re, *a_im, *b_re, *b_im, *c_re, *c_im, *log_dt, *dskip, *w2;
};

__global__ void __launch_bounds__(512, 1)
fused_kernel(const __grid_constant__ CUtensorMap tmX, const __grid_constant__ CUtensorMap tmW1,
             const __grid_constant__ CUtensorMap tmW2, const __grid_constant__ CUtensorMap tmW2b,
             const __grid_constant__ CUtensorMap tmYst, const __grid_constant__ CUtensorMap tmYld,
             const __grid_constant__ CUtensorMap tmOut, const Params P) {
  extern __shared__ __align__(1024) unsigned char smem_raw[];
  const uint32_t sb = smem_u32(smem_raw);
  const int tid = threadIdx.x, lane = tid & 31;
  const int b = blockIdx.x, mi = b >> 3, nj = b & 7;
  const uint32_t bars = sb + SM_BAR;
#define BAR(i) (bars + 8 * (i))
  const int kb0 = mi >> 1;
  if (tid == 128) {
    pf_map(&tmX); pf_map(&tmW1);
    for (int i = 0; i < 4; i++) { mbar_init(BAR(B_F1 + i), 1); mbar_init(BAR(B_E1 + i), 8); }
    fence_async_smem();
    TS1(32);
#pragma unroll 1
    for (int ks = 0; ks < 4; ks++) {
      const uint32_t slot = sb + ks * 40960;
      const int kb = (ks + kb0) & 7;
      mbar_expect(BAR(B_F1 + ks), 40960);
      tma_ld2(slot, &tmX, 64 * kb, 128 * mi, BAR(B_F1 + ks));
      for (int a = 0; a < 3; a++) tma_ld2(slot + 16384 + 8192 * a, &tmW1, 176 * nj + 64 * a, 64 * kb, BAR(B_F1 + ks));
    }
    TS1(33);
  } else if (tid == 160) {
    for (int i = 0; i < 6; i++) { mbar_init(BAR(B_F2 + i), 2); mbar_init(BAR(B_E2 + i), 4); }
    for (int i = B_MISC; i <= B_Y; i++) mbar_init(BAR(i), 1);
    mbar_init(BAR(B_OWN), 8);
    mbar_init(BAR(B_CS), 8);
    for (int i = 0; i < 3; i++) mbar_arrive(BAR(B_F2 + i));
    fence_async_smem();
    pf_map(&tmW2); pf_map(&tmW2b); pf_map(&tmYst); pf_map(&tmYld); pf_map(&tmOut);
  }
  const int warp = __shfl_sync(0xffffffffu, tid >> 5, 0);

  if (warp < 8) {
    const bool prod = (tid == 128);
    __syncthreads();
    if (prod) TS1(34);
    const int wg = warp >> 2, g = lane >> 2, q = lane & 3;
    const int mu = lane >> 3, r = lane & 7;
    {
      float acc[88];
#pragma unroll 1
      for (int ks = 0; ks < 8; ks++) {
        const int s = ks & 3;
        mbar_wait(BAR(B_F1 + s), ks >> 2);
        if (ks == 0) TS(0 + wg);
        const uint32_t slot = sb + s * 40960;
        const uint64_t da = mkdesc(slot + wg * 8192, 16, 1024, 1);
        const uint64_t db = mkdesc(slot + 16384, 8192, 1024, 1);
        wg_fence();
#pragma unroll
        for (int k = 0; k < 4; k++) wg_ss176(acc, da + 2 * k, db + 128 * k, (ks | k) != 0);
        wg_commit();
        if (ks > 0) {
          wg_wait<1>();
          const int sp = (ks - 1) & 3;
          if (lane == 0) mbar_arrive(BAR(B_E1 + sp));
          if (prod && ks < 7) {
            mbar_wait(BAR(B_E1 + sp), (ks - 1) >> 2);
            if (ks < 5) {
              if (ks == 1) mbar_wait(BAR(B_CS), 0);
              const uint32_t sl = sb + sp * 40960;
              const int kb = (ks + 3 + kb0) & 7;
              mbar_expect(BAR(B_F1 + sp), 40960);
              tma_ld2(sl, &tmX, 64 * kb, 128 * mi, BAR(B_F1 + sp));
              for (int a = 0; a < 3; a++) tma_ld2(sl + 16384 + 8192 * a, &tmW1, 176 * nj + 64 * a, 64 * kb, BAR(B_F1 + sp));
              if (ks == 2) asm volatile("cp.async.bulk.prefetch.L2.global [%0], %1;" ::"l"((const char*)P.w2 + 11008 * b), "r"(11008) : "memory");
            } else {
#pragma unroll 1
              for (int i = (ks == 5 ? 0 : 5); i < ks; i++) {
                const int c = i < 3 ? i : i - 3, sl = i < 3 ? nj : (nj == 0);
                mbar_expect(BAR(B_F2 + i), c < 2 ? 8192 : 6144);
                tma_ld2(sb + i * 8192, c < 2 ? &tmW2 : &tmW2b, 64 * nj, 176 * sl + 64 * c, BAR(B_F2 + i));
              }
            }
          }
          __syncwarp();
        }
      }
      wg_wait<0>();
      if (lane == 0) mbar_arrive(BAR(B_E1 + 3));
      TS(2 + wg);
      mbar_wait(BAR(B_MISC), 0);
      mbar_wait(BAR(B_E1 + 2), 1);
      if (tid == 0) TS1(26);
      const float m0 = -ldsf(sb + SM_STAT + (16 * warp + g) * 4), m1 = -ldsf(sb + SM_STAT + (16 * warp + g + 8) * 4);
      const uint32_t ha = sb + SM_HR + (mu >> 1) * 128 + r * 16, rg = 2 * warp + (mu & 1);
#pragma unroll
      for (int i = 0; i < 22; i += 2) {
        uint32_t v[4];
#pragma unroll
        for (int u = 0; u < 2; u++) {
          const float2 cs = lds64f(sb + SM_COLS + (8 * (i + u) + 2 * q) * 4);
          const float* a = acc + 4 * (i + u);
          v[2 * u] = pk_relu(fmaf(m0, cs.x, a[0]), fmaf(m0, cs.y, a[1]));
          v[2 * u + 1] = pk_relu(fmaf(m1, cs.x, a[2]), fmaf(m1, cs.y, a[3]));
        }
        stsm4(ha + (i >> 3) * 16384 + (i & 7) * 128 + rg * (i < 16 ? 1024 : 768), v[0], v[1], v[2], v[3]);
      }
      fence_async_smem();
      __syncwarp();
      if (tid == 0) TS1(27);
      if (lane == 0) {
        mbar_arrive(BAR(B_OWN));
        unsigned char* hb = g_h + (size_t)b * 45056;
        bulk_st(hb + warp * 2048, sb + SM_HR + warp * 2048, 2048);
        bulk_st(hb + 16384 + warp * 2048, sb + SM_HR + 16384 + warp * 2048, 2048);
        bulk_st(hb + 32768 + warp * 1536, sb + SM_HR + 32768 + warp * 1536, 1536);
        bulk_commit();
      }
    }
    if (wg == 1) {
      if (lane == 0) {
        bulk_wait0();
        red_release(&g_cnt[CNT_H(mi)], 2);
        if (warp == 4) {
          TS1(28);
          poll_cnt(&g_cnt[CNT_H(mi)], lds32(BAR(B_EPOCH)));
          TS1(18);
          fence_async_glb();
          TS1(19);
          int s = 3, ph = 1, c = 0;
          const unsigned char* hs = g_h + (size_t)(8 * mi + (nj == 0)) * 45056;
          const unsigned char* own = g_h + (size_t)b * 45056;
#pragma unroll 1
          for (int i = 3; i < 24; i++) {
            mbar_wait(BAR(B_E2 + s), ph);
            const uint32_t nb = c < 2 ? 16384 : 12288;
            mbar_expect(BAR(B_F2 + s), nb);
            bulk_ld(sb + SM_HR + s * 16384, hs, nb, BAR(B_F2 + s));
            hs += nb;
            if (hs == own) hs += 45056;
            if (++c == 3) c = 0;
            if (++s == 6) { s = 0; ph ^= 1; }
          }
        } else if (warp == 5) {
          int s = 0, ph = 0, c = 0, sl = 1 + (nj <= 1);
#pragma unroll 1
          for (int i = 6; i < 24; i++) {
            mbar_wait(BAR(B_E2 + s), ph);
            mbar_expect(BAR(B_F2 + s), c < 2 ? 8192 : 6144);
            tma_ld2(sb + s * 8192, c < 2 ? &tmW2 : &tmW2b, 64 * nj, 176 * sl + 64 * c, BAR(B_F2 + s));
            if (++c == 3) { c = 0; sl++; if (sl == nj) sl++; }
            if (++s == 6) { s = 0; ph ^= 1; }
          }
        } else if (warp == 6) {
          mbar_wait(BAR(B_E1 + 3), 1);
          mbar_expect(BAR(B_X), 16384);
          tma_ld2(sb + SM_XT, &tmX, 64 * nj, 128 * mi, BAR(B_X));
        }
      }
    } else {
      float acc[64];
      mbar_wait(BAR(B_OWN), 0);
      TS(6);
#pragma unroll 1
      for (int it = 0; it < 8; it++) {
        const int s0 = 3 * (it & 1), ph = (it >> 1) & 1;
#pragma unroll
        for (int c = 0; c < 3; c++) {
          const int s = s0 + c;
          mbar_wait(BAR(B_F2 + s), ph);
          const uint64_t da = mkdesc(sb + s * 8192, 8192, 1024, 1);
          const uint64_t db = mkdesc(sb + SM_HR + s * 16384, 128, c < 2 ? 1024 : 768, 0);
          wg_fence();
          wg_ss128t(acc, da, db, (it | c) != 0);
          wg_ss128t(acc, da + 128, db + 16, 1);
          wg_ss128t(acc, da + 256, db + 32, 1);
          if (c < 2) wg_ss128t(acc, da + 384, db + 48, 1);
          wg_commit();
          if (c == 2 && it == 0 && lane == 0) {
            bulk_wait0();
            red_release(&g_cnt[CNT_H(mi)], 2);
          }
          wg_wait<1>();
          if (lane == 0 && (it | c) != 0) mbar_arrive(BAR(B_E2 + (c ? s - 1 : 5 - s0)));
          __syncwarp();
        }
        if (it == 0) TS(7);
      }
      wg_wait<0>();
      TS(8);
      mbar_wait(BAR(B_X), 0);
      mbar_wait(BAR(B_Y), 0);
      TS(9);
      const uint32_t xa = sb + SM_XT + (8 * (mu >> 1) + r) * 128 + (((2 * warp + (mu & 1)) ^ r) << 4);
      const uint32_t ya = sb + SM_WK0 + (16 * warp + 8 * (mu & 1) + r) * 128;
#pragma unroll
      for (int i = 0; i < 16; i += 2) {
        uint32_t xv[4], yv[4], o[4];
        ldsm4t(xv, xa + i * 1024);
        ldsm4(yv, ya + (i >> 3) * 8192 + ((((i & 7) + (mu >> 1)) ^ r) << 4));
        const float2 r0 = lds64f(sb + SM_STAT + 512 + (8 * i + 2 * q) * 4), r1 = lds64f(sb + SM_STAT + 512 + (8 * i + 8 + 2 * q) * 4);
#pragma unroll
        for (int u = 0; u < 4; u++) {
          const float* a = acc + 4 * (i + (u >> 1)) + 2 * (u & 1);
          const float2 rr = (u >> 1) ? r1 : r0;
          o[u] = pk(fmaf(a[0], rr.x, blo(xv[u]) + blo(yv[u])), fmaf(a[1], rr.y, bhi(xv[u]) + bhi(yv[u])));
        }
        stsm4t(xa + i * 1024, o[0], o[1], o[2], o[3]);
      }
      fence_async_smem();
      nbar(4, 128);
      if (tid == 0) {
        tma_st2(&tmOut, sb + SM_XT, 64 * nj, 128 * mi);
        bulk_commit();
        bulk_wait0_read();
      }
      TS(10);
    }
  } else {
    const int st = tid - 256, wg = (warp >> 2) & 1, t128 = st & 127, w = warp & 3, sw = warp - 8;
    const int g = lane >> 2, q = lane & 3;
    uint32_t xr[16];
    {
      const uint32_t* xp = reinterpret_cast<const uint32_t*>(P.x) + (size_t)(128 * mi + 8 * nj) * 256 + st;
#pragma unroll
      for (int r = 0; r < 16; r++) xr[r] = __ldg(xp + ((r >> 3) * 64 + (r & 7)) * 256);
    }
    unsigned ep;
    asm volatile("ld.relaxed.gpu.global.u32 %0, [%1];" : "=r"(ep) : "l"(&g_cnt[CNT_PREP]) : "memory");
    unsigned short prm[2][8];
#pragma unroll
    for (int c = 0; c < 2; c++) {
      const int ch = 4 * b + 2 * wg + c, ix = ch * 128 + t128;
      prm[c][0] = __ldg((const unsigned short*)P.a_re + ix); prm[c][1] = __ldg((const unsigned short*)P.a_im + ix);
      prm[c][2] = __ldg((const unsigned short*)P.b_re + ix); prm[c][3] = __ldg((const unsigned short*)P.b_im + ix);
      prm[c][4] = __ldg((const unsigned short*)P.c_re + ix); prm[c][5] = __ldg((const unsigned short*)P.c_im + ix);
      prm[c][6] = __ldg((const unsigned short*)P.log_dt + ch);
    }
    const unsigned short dsk = __ldg((const unsigned short*)P.dskip + 4 * b + 2 * wg + (w >> 1));
#pragma unroll
    for (int i = 0; i < 4; i++)
      if (st + 256 * i < 928) sts128(sb + SM_KT + (st + 256 * i) * 16, 0, 0, 0, 0);
    if (st == 0) TS1(35);
    __syncthreads();
    if (st == 0) TS1(36);
    {
      const uint32_t red = sb + SM_WK0, wst = red + 2048 + sw * 128;
      float v[32];
#pragma unroll
      for (int r = 0; r < 16; r++) {
        const float a = blo(xr[r]), c = bhi(xr[r]);
        v[r] = a + c;
        v[16 + r] = fmaf(a, a, c * c);
      }
      xred<16>(v, lane);
      stsf(red + (sw * 32 + lane) * 4, v[0]);
      if (st == 0) TS1(37);
      nbar(1, 256);
      if (st == 0) TS1(38);
      float tot = 0.f;
#pragma unroll
      for (int i = 0; i < 8; i++) tot += ldsf(red + (i * 32 + lane) * 4);
      const float oth = __shfl_xor_sync(0xffffffffu, tot, 16);
      if (lane < 16) {
        const float mean = tot * (1.f / 512.f);
        const float var = fmaxf(fmaf(-mean, mean, oth * (1.f / 512.f)), 0.f);
        const float mb = bfr(mean);
        const float den = bfr(sqrtf(bfr(bfr(var) + 1e-5f)));
        const float rs = __fdividef(1.f, den);
        sts64f(wst + lane * 8, mb, rs);
        if (sw == 0) {
          float* gs = g_stat + 256 * mi + 64 * (lane >> 3) + 8 * nj + (lane & 7);
          gs[0] = mb; gs[128] = rs;
        }
      }
      __syncwarp();
      uint32_t o0[8], o1[8];
#pragma unroll
      for (int r = 0; r < 16; r += 2) {
        const float4 s2 = lds128f(wst + r * 8);
        o0[r >> 1] = pk(bfr(blo(xr[r]) - s2.x) * s2.y, bfr(blo(xr[r + 1]) - s2.z) * s2.w);
        o1[r >> 1] = pk(bfr(bhi(xr[r]) - s2.x) * s2.y, bfr(bhi(xr[r + 1]) - s2.z) * s2.w);
      }
      uint4* dp = reinterpret_cast<uint4*>(g_xnP + (size_t)(2 * st) * 2048 + nj * 256 + mi * 16);
      dp[0] = make_uint4(o0[0], o0[1], o0[2], o0[3]);
      dp[1] = make_uint4(o0[4], o0[5], o0[6], o0[7]);
      dp[256] = make_uint4(o1[0], o1[1], o1[2], o1[3]);
      dp[257] = make_uint4(o1[4], o1[5], o1[6], o1[7]);
      if (st == 0) TS1(39);
      const int par = (ep >> 7) & 1;
      ep = (ep & ~127u) + 128;
      if (mi == 0 && st < 176) g_colsum[(par ^ 1) * 1408 + 176 * nj + st] = 0.f;
      mbar_wait(BAR(B_F1), 0);
      const int row = 32 * (mi & 1) + lane;
#pragma unroll
      for (int c = 0; c < 3; c++) {
        const int cc = 3 * sw + c;
        const uint4 wv = lds128(sb + 16384 + (cc >> 3) * 8192 + row * 128 + (((cc & 7) ^ (row & 7)) << 4));
        v[8 * c + 0] = blo(wv.x); v[8 * c + 1] = bhi(wv.x); v[8 * c + 2] = blo(wv.y); v[8 * c + 3] = bhi(wv.y);
        v[8 * c + 4] = blo(wv.z); v[8 * c + 5] = bhi(wv.z); v[8 * c + 6] = blo(wv.w); v[8 * c + 7] = bhi(wv.w);
      }
#pragma unroll
      for (int i = 24; i < 32; i++) v[i] = 0.f;
      xred<16>(v, lane);
      if (lane == 0) mbar_arrive(BAR(B_CS));
      if (lane < 24 && 24 * sw + lane < 176) atomicAdd(&g_colsum[par * 1408 + 176 * nj + 24 * sw + lane], v[0]);
      if (st == 0) TS1(40);
      nbar(1, 256);
      if (st == 0) { sts32(BAR(B_EPOCH), ep); red_release(&g_cnt[CNT_PREP], 1); TS1(41); }
    }
    if (wg == 1) TS(12);
    const uint32_t wk = sb + (wg ? SM_WK1 : SM_WK0);
    {
      const uint32_t btb = sb + (wg ? SM_U + 2 * U_CH : SM_WK0);
#pragma unroll 1
      for (int c = 0; c < 2; c++) {
        float pf[7];
#pragma unroll
        for (int i = 0; i < 7; i++) pf[i] = __uint_as_float((uint32_t)(c ? prm[1][i] : prm[0][i]) << 16);
        const float dt = bfr(expf(pf[6]));
        const float ar = dt * pf[0], ai = dt * pf[1];
        const float arl = ar * 1.4426950408889634f;
        float2 wv = cmul(make_float2(pf[4], pf[5]), make_float2(dt * pf[2], dt * pf[3]));
        const float2 z1 = cexp_p(arl, ai, 1.f), z64 = cexp_p(arl, ai, 64.f), z256 = cexp_p(arl, ai, 256.f);
        sts128f(sb + SM_KT + (2 * wg + c) * KT_CH + 256 + t128 * 16, 8.f * arl, red2pi(8.f * ai), z64.x, z64.y);
        const uint32_t bt = btb + (t128 >> 2) * 784 + (t128 & 3) * 4 + c * 384;
        float2 v0, v4;
#pragma unroll
        for (int i = 0; i <= 8; i++) {
          if (i < 8) sts32(bt + i * 16, pk(wv.x, -wv.y));
          if (!(i & 1)) {
            const float2 t = cmul(wv, z256);
            sts32(bt + (i < 8 ? 8 + (i >> 1) : 18) * 16, pk(t.x, -t.y));
            if (i == 0) v0 = t;
            if (i == 4) v4 = t;
          }
          if (i < 8) wv = cmul(wv, z1);
        }
        v0 = cmul(v0, z256); v4 = cmul(v4, z256);
        sts32(bt + 12 * 16, pk(v0.x, -v0.y)); sts32(bt + 13 * 16, pk(v4.x, -v4.y));
        v0 = cmul(v0, z256); v4 = cmul(v4, z256);
        sts32(bt + 14 * 16, pk(v0.x, -v0.y)); sts32(bt + 15 * 16, pk(v4.x, -v4.y));
        v0 = cmul(v0, z256); sts32(bt + 16 * 16, pk(v0.x, -v0.y));
        v0 = cmul(v0, z256); sts32(bt + 17 * 16, pk(v0.x, -v0.y));
        v0 = cmul(v0, z256); sts32(bt + 20 * 16, pk(v0.x, -v0.y));
        v0 = cmul(v0, z256); sts32(bt + 21 * 16, pk(v0.x, -v0.y));
        v0 = cmul(v0, z256); sts32(bt + 19 * 16, pk(v0.x, -v0.y));
      }
      fence_async_smem();
      if (st == 128) TS1(42);
      nbar(2 + wg, 128);
      if (st == 128) TS1(43);
      float ka[24];
      const int j0 = 16 * (w & 1) + g;
      const float jf = (float)j0;
      const uint32_t kt = sb + SM_KT + (2 * wg + (w >> 1)) * KT_CH;
      const uint64_t dbt = mkdesc(btb, 784, 128, 0);
#pragma unroll
      for (int k4 = 0; k4 < 4; k4++) {
        uint32_t af[4][4];
#pragma unroll
        for (int k = 0; k < 4; k++) {
#pragma unroll
          for (int hh = 0; hh < 2; hh++) {
            const float4 p = lds128f(kt + 256 + (8 * (4 * k4 + k) + 4 * hh + q) * 16);
            const float m = ex2(p.x * jf), ph = p.y * jf;
            const float2 e = make_float2(m * __cosf(ph), m * __sinf(ph));
            const float2 e8 = cmul(e, make_float2(p.z, p.w));
            af[k][2 * hh] = pk(e.x, e.y);
            af[k][2 * hh + 1] = pk(e8.x, e8.y);
          }
        }
        wg_fence();
#pragma unroll
        for (int k = 0; k < 4; k++) {
          if (k4 == 0 && k == 0) wg_rs48<0>(ka, af[k][0], af[k][1], af[k][2], af[k][3], dbt);
          else wg_rs48<1>(ka, af[k][0], af[k][1], af[k][2], af[k][3], dbt + (4 * k4 + k) * 98);
        }
        wg_commit();
      }
      if (st == 128) TS1(44);
      wg_wait<0>();
      nbar(2 + wg, 128);
      if (st == 128) TS1(45);
      if (w == 0) {
        if (lane == 0) {
          poll_cnt(&g_cnt[CNT_PREP], ep);
          if (wg) TS1(17);
          if (wg == 0) {
            fence_async_glb();
            mbar_expect(BAR(B_MISC), 1024 + 704);
            bulk_ld(sb + SM_STAT, g_stat + 256 * mi, 1024, BAR(B_MISC));
            bulk_ld(sb + SM_COLS, g_colsum + (((ep >> 7) & 1) ^ 1) * 1408 + 176 * nj, 704, BAR(B_MISC));
          }
          mbar_expect(BAR(B_U + wg), 8192);
        }
        __syncwarp();
        if (lane < 16) {
          fence_async_glb();
          bulk_ld(sb + SM_U + (2 * wg + (lane >> 3)) * U_CH + (lane & 7) * U_PL + 128, g_xnP + (size_t)((4 * b + 2 * wg) * 8 + lane) * 256, 512, BAR(B_U + wg));
        }
        __syncwarp();
      }
      sts128(sb + SM_U + (2 * wg + (t128 >> 6)) * U_CH + ((t128 >> 3) & 7) * U_PL + (t128 & 7) * 16, 0, 0, 0, 0);
      float kv[12];
#pragma unroll
      for (int i = 0; i < 12; i++) kv[i] = (w >> 1) ? ka[12 + i] : ka[i];
#pragma unroll
      for (int h = 0; h < 2; h++) {
        const int j = j0 + 8 * h;
        float a = kv[2 * h], c = kv[2 * h + 1];
        const uint32_t p0 = kt + 256 + (8 * j + 2 * q) * 4;
        if (j == 0 && q == 0) { a += __uint_as_float((uint32_t)dsk << 16); sts16(p0 + 2, 0); }
        uint32_t ca = pk(c, a);
        sts16(p0, ca >> 16);
        sts32(p0 + 4, ca);
        sts16(p0 + 10, ca & 0xffff);
        a = kv[4 + 2 * h]; c = kv[5 + 2 * h];
        if (j == 31 && q == 1) c -= kv[8 + 2 * h];
        ca = pk(c, a);
        if (q < 2) {
          const uint32_t p1 = kt + 256 + (256 + 8 * j + 4 * q) * 4, aa = __byte_perm(ca, 0, 0x3232);
          if (j | q) { sts16(p1 - 4, aa); sts64(p1, aa, aa); }
          else { sts16(p1, aa); sts32(p1 + 4, aa); }
          sts32(p1 + 8, ca);
          sts16(p1 + 14, ca & 0xffff);
          if (j == 31 && q == 1) sts16(p1 + 12, 0);
        } else {
          sts16(kt + KT_Z5 + (32 * q + j) * 2, ca >> 16);
          sts16(kt + KT_Z3 + (32 * q + j) * 2, ca & 0xffff);
        }
        ca = pk(kv[9 + 2 * h], kv[8 + 2 * h]);
        if (!(q & 1)) {
          sts16((j | q) ? kt + KT_Z4 + (55 + 32 * q + j) * 2 : kt + KT_Z5 + 256, ca >> 16);
          sts16(kt + KT_Z4 + (87 + 32 * q + j) * 2, ca & 0xffff);
        } else if (q == 1 && j == 0) {
          sts16(kt + KT_Z4 + 183 * 2, ca & 0xffff);
        }
      }
      fence_async_smem();
      if (st == 128) TS1(46);
    }
    if (st == 128) TS1(24);
    mbar_wait(BAR(B_U + wg), 0);
    if (st == 128) TS1(25);
#pragma unroll 1
    for (int c = 0; c < 2; c++) {
      const uint32_t ub = sb + SM_U + (2 * wg + c) * U_CH;
      const uint32_t kt = sb + SM_KT + (2 * wg + c) * KT_CH;
#pragma unroll 1
      for (int ci = t128 - 23; ci <= 191; ci += 128) {
        float u[24];
#pragma unroll
        for (int k = 0; k < 3; k++) {
          const int cc = ci - 1 + k;
          const uint4 vv = lds128(ub + (cc & 7) * U_PL + ((cc >> 3) + 8) * 16);
          u[8 * k + 0] = blo(vv.x); u[8 * k + 1] = bhi(vv.x); u[8 * k + 2] = blo(vv.y); u[8 * k + 3] = bhi(vv.y);
          u[8 * k + 4] = blo(vv.z); u[8 * k + 5] = bhi(vv.z); u[8 * k + 6] = blo(vv.w); u[8 * k + 7] = bhi(vv.w);
        }
        float f2[8], s5[8];
#pragma unroll
        for (int i = 0; i < 8; i++) f2[i] = u[i + 4] + u[i + 5];
#pragma unroll
        for (int i = 0; i < 8; i++) s5[i] = (u[i + 6] + u[i + 7]) + (u[i + 8] + u[i + 9]) + u[i + 10];
        sts128(wk + WK_S5 + (ci + 23) * 16, pk(s5[0], s5[1]), pk(s5[2], s5[3]), pk(s5[4], s5[5]), pk(s5[6], s5[7]));
        if (ci >= -7)
          sts128(wk + WK_S3 + (ci + 7) * 16, pk(f2[0] + u[3], f2[1] + u[4]), pk(f2[2] + u[5], f2[3] + u[6]), pk(f2[4] + u[7], f2[5] + u[8]),
                 pk(f2[6] + u[9], f2[7] + u[10]));
        if (ci >= -8 && ci <= 127) {
          float s7[8];
#pragma unroll
          for (int i = 0; i < 8; i++) s7[i] = s5[i] + (u[i + 5] + u[i + 11]);
          sts128(wk + WK_S7 + (ci + 8) * 16, pk(s7[0], s7[1]), pk(s7[2], s7[3]), pk(s7[4], s7[5]), pk(s7[6], s7[7]));
#pragma unroll
          for (int i = 0; i < 8; i++) s7[i] += (u[i + 4] + u[i + 12]);
          sts128(wk + WK_S9 + (ci + 8) * 16, pk(s7[0], s7[1]), pk(s7[2], s7[3]), pk(s7[4], s7[5]), pk(s7[6], s7[7]));
          if (ci >= 0) sts128(wk + WK_F + (ci & 7) * 272 + (ci >> 3) * 16, pk(f2[0], f2[1]), pk(f2[2], f2[3]), pk(f2[4], f2[5]), pk(f2[6], f2[7]));
        }
      }
      if (st == 128) TS1(54 + 5 * c);
      fence_async_smem();
      nbar(2 + wg, 128);
      if (c == 0) { if (wg == 0) TS(14); mbar_wait(BAR(B_E1 + 3), 1); }
      if (st == 128) TS1(55 + 5 * c);
      float dacc[16], e01[8], e12[8], e23[8], e3[4];
      {
        const uint32_t pa = kt + (16 * w + g - 2 * q + 520 + 64) * 4;
        uint32_t hprev = lds32(pa);
#pragma unroll
        for (int blk = 0; blk < 6; blk++) {
          uint32_t h[13];
          h[0] = hprev;
          if (blk >= 2) wg_wait<1>();
#pragma unroll
          for (int i = 1; i < 13; i++) h[i] = lds32(pa - (12 * blk + i) * 32);
          hprev = h[12];
          wg_fence();
#pragma unroll
          for (int k = 0; k < 6; k++) {
            const int kap = 6 * blk + k;
            const uint64_t db = mkdesc(ub + (kap & 3) * 2 * U_PL + (kap >> 2) * 16, U_PL, 128, 0);
            if (kap == 0) wg_rs32<0>(dacc, h[2 * k + 1], h[2 * k], h[2 * k + 2], h[2 * k + 1], db);
            else wg_rs32<1>(dacc, h[2 * k + 1], h[2 * k], h[2 * k + 2], h[2 * k + 1], db);
          }
          wg_commit();
        }
      }
      {
        const int mu = lane >> 3, r = lane & 7, kk = r + 8 * (mu >> 1);
        const int cofs = 15 - kk + 2 * w + (mu & 1);
        const uint32_t a5 = wk + WK_S5 + cofs * 16;
        const uint32_t a3 = wk + WK_S3 + cofs * 16;
        const uint32_t a4 = wk + ((kk & 1) ? WK_S9 : WK_S7) + cofs * 16;
        uint32_t f[7][4];
        if (st == 128) TS1(56 + 5 * c);
        wg_wait<1>();
#pragma unroll
        for (int k = 0; k < 7; k++) ldsm4t(f[k], a5 + k * 256);
        wg_fence();
        wg_rs16<0>(e01, f[0][0], f[0][1], f[0][2], f[0][3], mkdesc(kt + KT_Z5 + 2 * (0 + 8), 16, 128, 0));
        wg_rs16<0>(e12, f[1][0], f[1][1], f[1][2], f[1][3], mkdesc(kt + KT_Z5 + 2 * (64 + 8 - 16), 16, 128, 0));
        wg_rs16<0>(e23, f[5][0], f[5][1], f[5][2], f[5][3], mkdesc(kt + KT_Z5 + 2 * (128 + 8 - 80), 16, 128, 0));
#pragma unroll
        for (int k = 2; k < 5; k++) wg_rs16<1>(e12, f[k][0], f[k][1], f[k][2], f[k][3], mkdesc(kt + KT_Z5 + 2 * (64 + 8 - 16 * k), 16, 128, 0));
        wg_rs16<1>(e23, f[6][0], f[6][1], f[6][2], f[6][3], mkdesc(kt + KT_Z5 + 2 * (128 + 8 - 96), 16, 128, 0));
        wg_commit();
        uint32_t f1[6][4];
        wg_wait<1>();
#pragma unroll
        for (int k = 0; k < 6; k++) ldsm4t(f1[k], a5 + (7 + k) * 256);
        wg_fence();
#pragma unroll
        for (int k = 0; k < 6; k++) {
          const int kap = 7 + k;
          if (kap <= 8) wg_rs16<1>(e23, f1[k][0], f1[k][1], f1[k][2], f1[k][3], mkdesc(kt + KT_Z5 + 2 * (128 + 8 - 16 * kap), 16, 128, 0));
          else if (kap == 9) wg_rs8<0>(e3, f1[k][0], f1[k][1], f1[k][2], f1[k][3], mkdesc(kt + KT_Z5 + 2 * (192 + 8 - 16 * kap), 16, 128, 0));
          else wg_rs8<1>(e3, f1[k][0], f1[k][1], f1[k][2], f1[k][3], mkdesc(kt + KT_Z5 + 2 * (192 + 8 - 16 * kap), 16, 128, 0));
        }
        wg_commit();
#pragma unroll
        for (int blk = 0; blk < 2; blk++) {
          uint32_t f3[6][4];
          wg_wait<1>();
#pragma unroll
          for (int k = 0; k < 6; k++) ldsm4t(f3[k], a3 + (6 * blk + k) * 256);
          wg_fence();
#pragma unroll
          for (int k = 0; k < 6; k++) {
            const int kap = 6 * blk + k;
            if (kap < 4) wg_rs16<1>(e12, f3[k][0], f3[k][1], f3[k][2], f3[k][3], mkdesc(kt + KT_Z3 + 2 * (64 - 8 - 16 * kap), 16, 128, 0));
            else if (kap < 8) wg_rs16<1>(e23, f3[k][0], f3[k][1], f3[k][2], f3[k][3], mkdesc(kt + KT_Z3 + 2 * (128 - 8 - 16 * kap), 16, 128, 0));
            else wg_rs8<1>(e3, f3[k][0], f3[k][1], f3[k][2], f3[k][3], mkdesc(kt + KT_Z3 + 2 * (192 - 8 - 16 * kap), 16, 128, 0));
          }
          wg_commit();
        }
#pragma unroll
        for (int blk = 0; blk < 2; blk++) {
          uint32_t f4[4][4];
          wg_wait<1>();
#pragma unroll
          for (int k = 0; k < 4; k++) ldsm4t(f4[k], a4 + (4 * blk + k) * 256);
          wg_fence();
#pragma unroll
          for (int k = 0; k < 4; k++) {
            const int kap = 4 * blk + k;
            if (kap < 4) wg_rs16<1>(e23, f4[k][0], f4[k][1], f4[k][2], f4[k][3], mkdesc(kt + KT_Z4 + 2 * (128 - 80 - 16 * kap), 16, 128, 0));
            else wg_rs8<1>(e3, f4[k][0], f4[k][1], f4[k][2], f4[k][3], mkdesc(kt + KT_Z4 + 2 * (192 - 80 - 16 * kap), 16, 128, 0));
          }
          wg_commit();
        }
        uint32_t ff[4];
        ldsm4t(ff, wk + WK_F + (2 * w + (mu & 1)) * 272 + (8 * (mu >> 1) + r) * 16);
        wg_wait<0>();
        if (st == 128) TS1(57 + 5 * c);
        const float kf = blo(lds32(kt + KT_Z5 + 256));
#pragma unroll
        for (int i = 0; i < 4; i++) { dacc[i] += e01[i]; dacc[4 + i] += e01[4 + i] + e12[i]; dacc[8 + i] += e12[4 + i] + e23[i]; dacc[12 + i] += e23[4 + i] + e3[i]; }
#pragma unroll
        for (int u = 0; u < 4; u++) {
          dacc[8 + 2 * u] = fmaf(kf, blo(ff[u]), dacc[8 + 2 * u]);
          dacc[9 + 2 * u] = fmaf(kf, bhi(ff[u]), dacc[9 + 2 * u]);
        }
        nbar(2 + wg, 128);
#pragma unroll
        for (int i = 0; i < 4; i += 2) {
          const int n = 8 * (i + (mu >> 1)) + r;
          stsm4t(wk + wg * 512 + n * 128 + (((2 * w + (mu & 1)) ^ r) << 4), pk(dacc[4 * i], dacc[4 * i + 1]), pk(dacc[4 * i + 2], dacc[4 * i + 3]),
                 pk(dacc[4 * i + 4], dacc[4 * i + 5]), pk(dacc[4 * i + 6], dacc[4 * i + 7]));
        }
        fence_async_smem();
        nbar(2 + wg, 128);
        if (t128 == 0) {
          tma_st2(&tmYst, wk + wg * 512, 0, (4 * b + 2 * wg + c) * 32);
          bulk_commit();
          if (c == 0) bulk_wait0_read();
          else { bulk_wait0(); if (wg) TS1(23); red_release(&g_cnt[CNT_Y(b >> 4)], 4); }
        }
        if (c == 0) nbar(2 + wg, 128);
      }
    }
    TS(21 + wg);
    nbar(1, 256);
    if (st == 0) {
      poll_cnt(&g_cnt[CNT_Y(nj)], ep);
      fence_async_glb();
      mbar_expect(BAR(B_Y), 16384);
      tma_ld2(sb + SM_WK0, &tmYld, 128 * mi, 64 * nj, BAR(B_Y));
      tma_ld2(sb + SM_WK0 + 8192, &tmYld, 128 * mi + 64, 64 * nj, BAR(B_Y));
      TS1(20);
    }
  }
}

typedef CUresult (*PFN_enc)(CUtensorMap*, CUtensorMapDataType, cuuint32_t, void*, const cuuint64_t*, const cuuint64_t*, const cuuint32_t*,
                            const cuuint32_t*, CUtensorMapInterleave, CUtensorMapSwizzle, CUtensorMapL2promotion, CUtensorMapFloatOOBfill);

static void make_map(PFN_enc enc, CUtensorMap* m, const void* ptr, uint64_t cols, uint64_t rows, uint32_t bc, uint32_t br, bool sw) {
  cuuint64_t dims[2] = {cols, rows};
  cuuint64_t strides[1] = {cols * 2};
  cuuint32_t box[2] = {bc, br};
  cuuint32_t es[2] = {1, 1};
  enc(m, CU_TENSOR_MAP_DATA_TYPE_BFLOAT16, 2, const_cast<void*>(ptr), dims, strides, box, es, CU_TENSOR_MAP_INTERLEAVE_NONE,
      sw ? CU_TENSOR_MAP_SWIZZLE_128B : CU_TENSOR_MAP_SWIZZLE_NONE, CU_TENSOR_MAP_L2_PROMOTION_L2_128B, CU_TENSOR_MAP_FLOAT_OOB_FILL_NONE);
}

extern "C" void kernel_launch(void* const* d_in, const int* in_sizes, int n_in, void* d_out, int out_size) {
  (void)in_sizes; (void)n_in; (void)out_size;
  static PFN_enc enc = nullptr;
  static void* py = nullptr;
  if (!enc) {
    void* fn = nullptr;
    cudaDriverEntryPointQueryResult qr;
    cudaGetDriverEntryPoint("cuTensorMapEncodeTiled", &fn, cudaEnableDefault, &qr);
    enc = (PFN_enc)fn;
    cudaGetSymbolAddress(&py, g_yT);
    cudaFuncSetAttribute(fused_kernel, cudaFuncAttributeMaxDynamicSharedMemorySize, SM_TOTAL);
  }
  CUtensorMap tmX, tmW1, tmW2, tmW2b, tmYst, tmYld, tmOut;
  make_map(enc, &tmX, d_in[0], 512, 2048, 64, 128, true);
  make_map(enc, &tmW1, d_in[10], 1376, 512, 64, 64, true);
  make_map(enc, &tmW2, d_in[11], 512, 1376, 64, 64, true);
  make_map(enc, &tmW2b, d_in[11], 512, 1376, 64, 48, true);
  make_map(enc, &tmYst, py, 64, 512 * 32, 64, 32, true);
  make_map(enc, &tmYld, py, 2048, 512, 64, 64, true);
  make_map(enc, &tmOut, d_out, 512, 2048, 64, 128, true);
  Params P;
  P.x = (const bf16*)d_in[0]; P.a_re = (const bf16*)d_in[1]; P.a_im = (const bf16*)d_in[2];
  P.b_re = (const bf16*)d_in[3]; P.b_im = (const bf16*)d_in[4]; P.c_re = (const bf16*)d_in[5]; P.c_im = (const bf16*)d_in[6];
  P.log_dt = (const bf16*)d_in[7]; P.dskip = (const bf16*)d_in[8]; P.w2 = (const bf16*)d_in[11];
  fused_kernel<<<128, 512, SM_TOTAL, cudaStreamPerThread>>>(tmX, tmW1, tmW2, tmW2b, tmYst, tmYld, tmOut, P);
}
```

```cpp
#include <cuda_runtime.h>
#include <cuda_bf16.h>
#include <cuda.h>
#include <stdint.h>

typedef __nv_bfloat16 bf16;

__device__ __align__(1024) bf16 g_xnP[512 * 2048];
__device__ __align__(1024) unsigned char g_h[16 * 8 * 45056];
__device__ __align__(1024) bf16 g_yT[512 * 2048];
__device__ __align__(128) float g_stat[128 * 32];
__device__ __align__(128) float g_colsum[2 * 1408];
__device__ __align__(128) unsigned g_cnt[36 * 32];
#define TS(k)
#define TS1(k)
#define CNT_P(c) (32 * (c))
#define CNT_CS(j) (128 + 32 * (j))
#define CNT_H(i) (384 + 32 * (i))
#define CNT_Y(j) (896 + 32 * (j))

constexpr int SM_HR = 49152;
constexpr int SM_STAT = 22528, SM_COLS = 23552;
constexpr int SM_S0 = 147456, BLK = 20592;
constexpr int U_PL = 656, O_KT = 5248, O_WK = 9584, O_BT = 8544;
constexpr int KT_Z5 = 2672, KT_Z3 = 3312, KT_Z4 = 3968;
constexpr int WK_S5 = 0, WK_S3 = 3456, WK_S9 = 6656, WK_S7 = 8832;
constexpr int SM_XT = SM_HR, SM_YT = SM_S0 + 41984;
constexpr int SM_RED = 229824, SM_CSST = 230848, SM_STST = 231616, SM_BAR = 231744;
constexpr int SM_TOTAL = 232064;
#define GATE 7
constexpr int B_F1 = 0, B_E1 = 8, B_F2 = 16, B_E2 = 22, B_MISC = 28, B_OWN = 29, B_X = 30, B_Y = 31, B_U = 32, B_LN = 34;
constexpr int SM_LNX = 73728 + ((0x8618 >> 4) & 3) * 16384;

__device__ __forceinline__ uint32_t smem_u32(const void* p) { return (uint32_t)__cvta_generic_to_shared(p); }
__device__ __forceinline__ void mbar_init(uint32_t bar, uint32_t cnt) { asm volatile("mbarrier.init.shared::cta.b64 [%0], %1;" ::"r"(bar), "r"(cnt) : "memory"); }
__device__ __forceinline__ void mbar_expect(uint32_t bar, uint32_t bytes) { asm volatile("mbarrier.arrive.expect_tx.shared::cta.b64 _, [%0], %1;" ::"r"(bar), "r"(bytes) : "memory"); }
__device__ __forceinline__ void mbar_arrive(uint32_t bar) { asm volatile("mbarrier.arrive.shared::cta.b64 _, [%0];" ::"r"(bar) : "memory"); }
__device__ __forceinline__ bool mbar_try(uint32_t bar, uint32_t par) {
  uint32_t ok;
  asm volatile("{\n.reg .pred p;\nmbarrier.try_wait.parity.shared::cta.b64 p, [%1], %2;\nselp.u32 %0,1,0,p;\n}" : "=r"(ok) : "r"(bar), "r"(par) : "memory");
  return ok;
}
__device__ __forceinline__ void mbar_wait(uint32_t bar, uint32_t par) {
  asm volatile("{\n.reg .pred p;\n.reg .u32 c;\nmov.u32 c,0;\nLW:\nmbarrier.try_wait.parity.shared::cta.b64 p,[%0],%1;\n@p bra LD;\n"
               "add.u32 c,c,1;\nsetp.lt.u32 p,c,0x400000;\n@p bra LW;\nLD:\n}" ::"r"(bar), "r"(par) : "memory");
}
__device__ __forceinline__ unsigned ld_rlx(const unsigned* p) { unsigned v; asm volatile("ld.relaxed.gpu.global.u32 %0, [%1];" : "=r"(v) : "l"(p) : "memory"); return v; }
__device__ __forceinline__ void poll_cnt(const unsigned* p, unsigned target) {
#pragma unroll 1
  for (int i = 0; i < (1 << 22); i++)
    if ((int)(ld_rlx(p) - target) >= 0) break;
}
template <int N, int OFF> __device__ __forceinline__ void xred(float* v, int lane) {
  const bool up = lane & OFF;
#pragma unroll
  for (int i = 0; i < N; i++) {
    const float snd = up ? v[i] : v[i + N], kp = up ? v[i + N] : v[i];
    v[i] = kp + __shfl_xor_sync(0xffffffffu, snd, OFF);
  }
  if constexpr (N > 1) xred<N / 2, OFF / 2>(v, lane);
}
__device__ __forceinline__ bool elect_one() { uint32_t p; asm volatile("{\n.reg .pred P;\nelect.sync _|P, 0xffffffff;\nselp.u32 %0,1,0,P;\n}" : "=r"(p)); return p; }
__device__ __forceinline__ void red_add(unsigned* p, unsigned v) { asm volatile("red.relaxed.gpu.global.add.u32 [%0], %1;" ::"l"(p), "r"(v) : "memory"); }
__device__ __forceinline__ void bulk_red_f32(void* dst, uint32_t src, uint32_t bytes) {
  asm volatile("cp.reduce.async.bulk.global.shared::cta.bulk_group.add.f32 [%0], [%1], %2;" ::"l"(dst), "r"(src), "r"(bytes) : "memory");
}
__device__ __forceinline__ void nbar_arrive(int id, int n) { asm volatile("bar.arrive %0, %1;" ::"r"(id), "r"(n) : "memory"); }
__device__ __forceinline__ void mma16816(float* d, uint32_t a0, uint32_t a1, uint32_t a2, uint32_t a3, uint32_t b0) {
  asm volatile("mma.sync.aligned.m16n8k16.row.col.f32.bf16.bf16.f32 {%0,%1,%2,%3},{%4,%5,%6,%7},{%8,%8},{%0,%1,%2,%3};"
               : "+f"(d[0]), "+f"(d[1]), "+f"(d[2]), "+f"(d[3]) : "r"(a0), "r"(a1), "r"(a2), "r"(a3), "r"(b0));
}
__device__ __forceinline__ uint32_t lds16(uint32_t a) { unsigned short v; asm volatile("ld.shared.u16 %0,[%1];" : "=h"(v) : "r"(a) : "memory"); return v; }
__device__ __forceinline__ uint32_t hsub2(uint32_t a, uint32_t b) { uint32_t r; asm("sub.rn.bf16x2 %0,%1,%2;" : "=r"(r) : "r"(a), "r"(b)); return r; }
__device__ __forceinline__ void fence_async_glb() { asm volatile("fence.proxy.async.global;" ::: "memory"); }
__device__ __forceinline__ void pf_map(const CUtensorMap* m) { asm volatile("prefetch.tensormap [%0];" ::"l"(m) : "memory"); }
__device__ __forceinline__ void bulk_st(void* dst, uint32_t src, uint32_t bytes) {
  asm volatile("cp.async.bulk.global.shared::cta.bulk_group [%0], [%1], %2;" ::"l"(dst), "r"(src), "r"(bytes) : "memory");
}
__device__ __forceinline__ void sts16(uint32_t a, uint32_t v) { asm volatile("st.shared.u16 [%0],%1;" ::"r"(a), "h"((unsigned short)v) : "memory"); }
__device__ __forceinline__ void sts64(uint32_t a, uint32_t x, uint32_t y) { asm volatile("st.shared.v2.u32 [%0],{%1,%2};" ::"r"(a), "r"(x), "r"(y) : "memory"); }
__device__ __forceinline__ uint32_t pk_relu(float lo, float hi) { uint32_t r; asm("cvt.rn.relu.bf16x2.f32 %0,%1,%2;" : "=r"(r) : "f"(hi), "f"(lo)); return r; }
__device__ __forceinline__ void fence_async_smem() { asm volatile("fence.proxy.async.shared::cta;" ::: "memory"); }
__device__ __forceinline__ void tma_ld2(uint32_t dst, const CUtensorMap* m, int c0, int c1, uint32_t bar) {
  asm volatile("cp.async.bulk.tensor.2d.shared::cluster.global.mbarrier::complete_tx::bytes [%0], [%1, {%3, %4}], [%2];" ::"r"(dst), "l"(m), "r"(bar), "r"(c0), "r"(c1) : "memory");
}
__device__ __forceinline__ void tma_st2(const CUtensorMap* m, uint32_t src, int c0, int c1) {
  asm volatile("cp.async.bulk.tensor.2d.global.shared::cta.bulk_group [%0, {%2, %3}], [%1];" ::"l"(m), "r"(src), "r"(c0), "r"(c1) : "memory");
}
__device__ __forceinline__ void bulk_ld(uint32_t dst, const void* src, uint32_t bytes, uint32_t bar) {
  asm volatile("cp.async.bulk.shared::cluster.global.mbarrier::complete_tx::bytes [%0], [%1], %2, [%3];" ::"r"(dst), "l"(src), "r"(bytes), "r"(bar) : "memory");
}
__device__ __forceinline__ void bulk_commit() { asm volatile("cp.async.bulk.commit_group;" ::: "memory"); }
__device__ __forceinline__ void bulk_wait0() { asm volatile("cp.async.bulk.wait_group 0;" ::: "memory"); }
__device__ __forceinline__ void bulk_wait0_read() { asm volatile("cp.async.bulk.wait_group.read 0;" ::: "memory"); }
__device__ __forceinline__ void nbar(int id, int n) { asm volatile("bar.sync %0, %1;" ::"r"(id), "r"(n) : "memory"); }
__device__ __forceinline__ void wg_fence() { asm volatile("wgmma.fence.sync.aligned;" ::: "memory"); }
__device__ __forceinline__ void wg_commit() { asm volatile("wgmma.commit_group.sync.aligned;" ::: "memory"); }
template <int n> __device__ __forceinline__ void wg_wait() { asm volatile("wgmma.wait_group.sync.aligned %0;" ::"n"(n) : "memory"); }
constexpr unsigned HI_SW = 64u | (1u << 30);
__device__ __forceinline__ void ldsm4(uint32_t* r, uint32_t a) { asm volatile("ldmatrix.sync.aligned.m8n8.x4.shared.b16 {%0,%1,%2,%3},[%4];" : "=r"(r[0]), "=r"(r[1]), "=r"(r[2]), "=r"(r[3]) : "r"(a) : "memory"); }
__device__ __forceinline__ void ldsm4t(uint32_t* r, uint32_t a) { asm volatile("ldmatrix.sync.aligned.m8n8.x4.trans.shared.b16 {%0,%1,%2,%3},[%4];" : "=r"(r[0]), "=r"(r[1]), "=r"(r[2]), "=r"(r[3]) : "r"(a) : "memory"); }
__device__ __forceinline__ void stsm4(uint32_t a, uint32_t r0, uint32_t r1, uint32_t r2, uint32_t r3) { asm volatile("stmatrix.sync.aligned.m8n8.x4.shared.b16 [%0],{%1,%2,%3,%4};" ::"r"(a), "r"(r0), "r"(r1), "r"(r2), "r"(r3) : "memory"); }
__device__ __forceinline__ void stsm4t(uint32_t a, uint32_t r0, uint32_t r1, uint32_t r2, uint32_t r3) { asm volatile("stmatrix.sync.aligned.m8n8.x4.trans.shared.b16 [%0],{%1,%2,%3,%4};" ::"r"(a), "r"(r0), "r"(r1), "r"(r2), "r"(r3) : "memory"); }
__device__ __forceinline__ uint32_t lds32(uint32_t a) { uint32_t v; asm volatile("ld.shared.u32 %0,[%1];" : "=r"(v) : "r"(a) : "memory"); return v; }
__device__ __forceinline__ float ldsf(uint32_t a) { float v; asm volatile("ld.shared.f32 %0,[%1];" : "=f"(v) : "r"(a) : "memory"); return v; }
__device__ __forceinline__ float2 lds64f(uint32_t a) { float2 v; asm volatile("ld.shared.v2.f32 {%0,%1},[%2];" : "=f"(v.x), "=f"(v.y) : "r"(a) : "memory"); return v; }
__device__ __forceinline__ float4 lds128f(uint32_t a) { float4 v; asm volatile("ld.shared.v4.f32 {%0,%1,%2,%3},[%4];" : "=f"(v.x), "=f"(v.y), "=f"(v.z), "=f"(v.w) : "r"(a) : "memory"); return v; }
__device__ __forceinline__ uint4 lds128(uint32_t a) { uint4 v; asm volatile("ld.shared.v4.u32 {%0,%1,%2,%3},[%4];" : "=r"(v.x), "=r"(v.y), "=r"(v.z), "=r"(v.w) : "r"(a) : "memory"); return v; }
__device__ __forceinline__ void sts32(uint32_t a, uint32_t v) { asm volatile("st.shared.u32 [%0],%1;" ::"r"(a), "r"(v) : "memory"); }
__device__ __forceinline__ void stsf(uint32_t a, float v) { asm volatile("st.shared.f32 [%0],%1;" ::"r"(a), "f"(v) : "memory"); }
__device__ __forceinline__ void sts64f(uint32_t a, float x, float y) { asm volatile("st.shared.v2.f32 [%0],{%1,%2};" ::"r"(a), "f"(x), "f"(y) : "memory"); }
__device__ __forceinline__ void sts128f(uint32_t a, float x, float y, float z, float w) { asm volatile("st.shared.v4.f32 [%0],{%1,%2,%3,%4};" ::"r"(a), "f"(x), "f"(y), "f"(z), "f"(w) : "memory"); }
__device__ __forceinline__ void sts128(uint32_t a, uint32_t x, uint32_t y, uint32_t z, uint32_t w) { asm volatile("st.shared.v4.u32 [%0],{%1,%2,%3,%4};" ::"r"(a), "r"(x), "r"(y), "r"(z), "r"(w) : "memory"); }
__device__ __forceinline__ uint32_t pk(float lo, float hi) { uint32_t r; asm("cvt.rn.bf16x2.f32 %0,%1,%2;" : "=r"(r) : "f"(hi), "f"(lo)); return r; }
__device__ __forceinline__ float blo(uint32_t v) { return __uint_as_float(v << 16); }
__device__ __forceinline__ float bhi(uint32_t v) { return __uint_as_float(v & 0xffff0000u); }
__device__ __forceinline__ float bfr(float x) { return __bfloat162float(__float2bfloat16_rn(x)); }
__device__ __forceinline__ float ex2(float x) { float r; asm("ex2.approx.ftz.f32 %0,%1;" : "=f"(r) : "f"(x)); return r; }
__device__ __forceinline__ float red2pi(float x) {
  float k = rintf(x * 0.15915494309189535f);
  x = fmaf(k, -6.2831854820251465f, x);
  return fmaf(k, 1.7484555e-7f, x);
}
__device__ __forceinline__ float2 cmul(float2 a, float2 b) { return make_float2(fmaf(a.x, b.x, -a.y * b.y), fmaf(a.x, b.y, a.y * b.x)); }
__device__ __forceinline__ float2 cexp_p(float arl, float ai, float p) {
  float m = ex2(arl * p), ph = red2pi(ai * p);
  return make_float2(m * __cosf(ph), m * __sinf(ph));
}
template<unsigned HA, unsigned HB> __device__ __forceinline__ void wg_ss176(float* d, uint32_t la, uint32_t lb, int sc){
  asm volatile("{\n.reg .pred p;\n.reg .b64 da,db;\nsetp.ne.b32 p,%90,0;\nmov.b64 da,{%88,%91};\nmov.b64 db,{%89,%92};\nwgmma.mma_async.sync.aligned.m64n176k16.f32.bf16.bf16 {%0,%1,%2,%3,%4,%5,%6,%7,%8,%9,%10,%11,%12,%13,%14,%15,%16,%17,%18,%19,%20,%21,%22,%23,%24,%25,%26,%27,%28,%29,%30,%31,%32,%33,%34,%35,%36,%37,%38,%39,%40,%41,%42,%43,%44,%45,%46,%47,%48,%49,%50,%51,%52,%53,%54,%55,%56,%57,%58,%59,%60,%61,%62,%63,%64,%65,%66,%67,%68,%69,%70,%71,%72,%73,%74,%75,%76,%77,%78,%79,%80,%81,%82,%83,%84,%85,%86,%87},da,db,p,1,1,0,1;\n}"
    : "+f"(d[0]),"+f"(d[1]),"+f"(d[2]),"+f"(d[3]),"+f"(d[4]),"+f"(d[5]),"+f"(d[6]),"+f"(d[7]),"+f"(d[8]),"+f"(d[9]),"+f"(d[10]),"+f"(d[11]),"+f"(d[12]),"+f"(d[13]),"+f"(d[14]),"+f"(d[15]),"+f"(d[16]),"+f"(d[17]),"+f"(d[18]),"+f"(d[19]),"+f"(d[20]),"+f"(d[21]),"+f"(d[22]),"+f"(d[23]),"+f"(d[24]),"+f"(d[25]),"+f"(d[26]),"+f"(d[27]),"+f"(d[28]),"+f"(d[29]),"+f"(d[30]),"+f"(d[31]),"+f"(d[32]),"+f"(d[33]),"+f"(d[34]),"+f"(d[35]),"+f"(d[36]),"+f"(d[37]),"+f"(d[38]),"+f"(d[39]),"+f"(d[40]),"+f"(d[41]),"+f"(d[42]),"+f"(d[43]),"+f"(d[44]),"+f"(d[45]),"+f"(d[46]),"+f"(d[47]),"+f"(d[48]),"+f"(d[49]),"+f"(d[50]),"+f"(d[51]),"+f"(d[52]),"+f"(d[53]),"+f"(d[54]),"+f"(d[55]),"+f"(d[56]),"+f"(d[57]),"+f"(d[58]),"+f"(d[59]),"+f"(d[60]),"+f"(d[61]),"+f"(d[62]),"+f"(d[63]),"+f"(d[64]),"+f"(d[65]),"+f"(d[66]),"+f"(d[67]),"+f"(d[68]),"+f"(d[69]),"+f"(d[70]),"+f"(d[71]),"+f"(d[72]),"+f"(d[73]),"+f"(d[74]),"+f"(d[75]),"+f"(d[76]),"+f"(d[77]),"+f"(d[78]),"+f"(d[79]),"+f"(d[80]),"+f"(d[81]),"+f"(d[82]),"+f"(d[83]),"+f"(d[84]),"+f"(d[85]),"+f"(d[86]),"+f"(d[87])
    : "r"(la),"r"(lb),"r"(sc),"n"(HA),"n"(HB));
}
template<unsigned HA, unsigned HB> __device__ __forceinline__ void wg_ss128t(float* d, uint32_t la, uint32_t lb, int sc){
  asm volatile("{\n.reg .pred p;\n.reg .b64 da,db;\nsetp.ne.b32 p,%66,0;\nmov.b64 da,{%64,%67};\nmov.b64 db,{%65,%68};\nwgmma.mma_async.sync.aligned.m64n128k16.f32.bf16.bf16 {%0,%1,%2,%3,%4,%5,%6,%7,%8,%9,%10,%11,%12,%13,%14,%15,%16,%17,%18,%19,%20,%21,%22,%23,%24,%25,%26,%27,%28,%29,%30,%31,%32,%33,%34,%35,%36,%37,%38,%39,%40,%41,%42,%43,%44,%45,%46,%47,%48,%49,%50,%51,%52,%53,%54,%55,%56,%57,%58,%59,%60,%61,%62,%63},da,db,p,1,1,1,0;\n}"
    : "+f"(d[0]),"+f"(d[1]),"+f"(d[2]),"+f"(d[3]),"+f"(d[4]),"+f"(d[5]),"+f"(d[6]),"+f"(d[7]),"+f"(d[8]),"+f"(d[9]),"+f"(d[10]),"+f"(d[11]),"+f"(d[12]),"+f"(d[13]),"+f"(d[14]),"+f"(d[15]),"+f"(d[16]),"+f"(d[17]),"+f"(d[18]),"+f"(d[19]),"+f"(d[20]),"+f"(d[21]),"+f"(d[22]),"+f"(d[23]),"+f"(d[24]),"+f"(d[25]),"+f"(d[26]),"+f"(d[27]),"+f"(d[28]),"+f"(d[29]),"+f"(d[30]),"+f"(d[31]),"+f"(d[32]),"+f"(d[33]),"+f"(d[34]),"+f"(d[35]),"+f"(d[36]),"+f"(d[37]),"+f"(d[38]),"+f"(d[39]),"+f"(d[40]),"+f"(d[41]),"+f"(d[42]),"+f"(d[43]),"+f"(d[44]),"+f"(d[45]),"+f"(d[46]),"+f"(d[47]),"+f"(d[48]),"+f"(d[49]),"+f"(d[50]),"+f"(d[51]),"+f"(d[52]),"+f"(d[53]),"+f"(d[54]),"+f"(d[55]),"+f"(d[56]),"+f"(d[57]),"+f"(d[58]),"+f"(d[59]),"+f"(d[60]),"+f"(d[61]),"+f"(d[62]),"+f"(d[63])
    : "r"(la),"r"(lb),"r"(sc),"n"(HA),"n"(HB));
}
template<int SC> __device__ __forceinline__ void wg_rs48(float* d, uint32_t a0, uint32_t a1, uint32_t a2, uint32_t a3, uint32_t lb){
  asm volatile("{\n.reg .b64 db;\nmov.b64 db,{%28,8};\nwgmma.mma_async.sync.aligned.m64n48k16.f32.bf16.bf16 {%0,%1,%2,%3,%4,%5,%6,%7,%8,%9,%10,%11,%12,%13,%14,%15,%16,%17,%18,%19,%20,%21,%22,%23},{%24,%25,%26,%27},db,%29,1,1,0;\n}"
    : "+f"(d[0]),"+f"(d[1]),"+f"(d[2]),"+f"(d[3]),"+f"(d[4]),"+f"(d[5]),"+f"(d[6]),"+f"(d[7]),"+f"(d[8]),"+f"(d[9]),"+f"(d[10]),"+f"(d[11]),"+f"(d[12]),"+f"(d[13]),"+f"(d[14]),"+f"(d[15]),"+f"(d[16]),"+f"(d[17]),"+f"(d[18]),"+f"(d[19]),"+f"(d[20]),"+f"(d[21]),"+f"(d[22]),"+f"(d[23])
    : "r"(a0),"r"(a1),"r"(a2),"r"(a3),"r"(lb),"n"(SC));
}
template<int SC> __device__ __forceinline__ void wg_rs32(float* d, uint32_t a0, uint32_t a1, uint32_t a2, uint32_t a3, uint32_t lb){
  asm volatile("{\n.reg .b64 db;\nmov.b64 db,{%20,8};\nwgmma.mma_async.sync.aligned.m64n32k16.f32.bf16.bf16 {%0,%1,%2,%3,%4,%5,%6,%7,%8,%9,%10,%11,%12,%13,%14,%15},{%16,%17,%18,%19},db,%21,1,1,0;\n}"
    : "+f"(d[0]),"+f"(d[1]),"+f"(d[2]),"+f"(d[3]),"+f"(d[4]),"+f"(d[5]),"+f"(d[6]),"+f"(d[7]),"+f"(d[8]),"+f"(d[9]),"+f"(d[10]),"+f"(d[11]),"+f"(d[12]),"+f"(d[13]),"+f"(d[14]),"+f"(d[15])
    : "r"(a0),"r"(a1),"r"(a2),"r"(a3),"r"(lb),"n"(SC));
}

struct Params {
  const bf16 *x, *a_re, *a_im, *b_re, *b_im, *c_re, *c_im, *log_dt, *dskip, *w1, *w2;
};

__global__ void __launch_bounds__(512, 1)
fused_kernel(const Params P, const __grid_constant__ CUtensorMap tmX, const __grid_constant__ CUtensorMap tmW1,
             const __grid_constant__ CUtensorMap tmW2, const __grid_constant__ CUtensorMap tmW2b,
             const __grid_constant__ CUtensorMap tmYst, const __grid_constant__ CUtensorMap tmYld,
             const __grid_constant__ CUtensorMap tmOut, const __grid_constant__ CUtensorMap tmXn) {
  extern __shared__ __align__(1024) unsigned char smem_raw[];
  const uint32_t sb = smem_u32(smem_raw);
  const int tid = threadIdx.x, lane = tid & 31;
  const int b = blockIdx.x, mi = b >> 3, nj = b & 7;
  const uint32_t bars = sb + SM_BAR;
#define BAR(i) (bars + 8 * (i))
  const int warp = __shfl_sync(0xffffffffu, tid >> 5, 0);
  {
    if (warp == 4) {
      const bool el = elect_one();
      if (el) {
        mbar_init(BAR(B_F1), 1); mbar_init(BAR(B_F1 + 1), 1); mbar_init(BAR(B_LN), 1);
        fence_async_smem();
        mbar_expect(BAR(B_LN), 16384);
        bulk_ld(sb + SM_LNX, P.x + (size_t)(128 * mi + 8 * nj) * 512, 8192, BAR(B_LN));
        bulk_ld(sb + SM_LNX + 8192, P.x + (size_t)(128 * mi + 64 + 8 * nj) * 512, 8192, BAR(B_LN));
      }
      __syncwarp();
      nbar_arrive(0, 512);
      if (el) {
#pragma unroll 1
        for (int s = 0; s < 2; s++) {
          mbar_expect(BAR(B_F1 + s), 40960);
          tma_ld2(sb + 73728 + ((0x8618 >> (2 * s)) & 3) * 16384, &tmX, 64 * s, 128 * mi, BAR(B_F1 + s));
#pragma unroll
          for (int a = 0; a < 3; a++) tma_ld2(sb + s * 24576 + a * 8192, &tmW1, 176 * nj + 64 * a, 64 * s, BAR(B_F1 + s));
          TS1(33 + s);
        }
      }
      __syncwarp();
    }
    if (warp > 4 && warp < 8 && elect_one()) {
      const int s = warp - 5;
      if (s == 0) { pf_map(&tmX); pf_map(&tmW1); }
      const unsigned long long cn = s == 0 ? 0x88888444444ull : s == 1 ? 0x44222222888ull : 0x04411814444ull;
#pragma unroll
      for (int i = 0; i < 11; i++) if (i < 10 || s < 2) mbar_init(BAR(2 + 11 * s + i), (uint32_t)(cn >> (4 * i)) & 15);
      if (s == 1) { mbar_arrive(BAR(B_F2)); mbar_arrive(BAR(B_F2 + 1)); mbar_arrive(BAR(B_F2 + 2)); }
      fence_async_smem();
      if (s == 1) { pf_map(&tmXn); pf_map(&tmW2); pf_map(&tmW2b); }
      if (s == 2) { pf_map(&tmYst); pf_map(&tmYld); pf_map(&tmOut); }
    }
  }
  unsigned e0;
  if (warp >= 8) e0 = ld_rlx(&g_cnt[CNT_Y(b >> 4)]);
#define EPOCH ((e0 & ~127u) + 128)
  unsigned short prm[2][8];
  uint4 wv[8];
  if (warp >= 8) {
    {
      const int cw = warp - 13, g = lane >> 2;
      const bool ok = cw >= 0 && 64 * cw + 8 * g < (nj == 7 ? 144 : 176);
      const uint4* wp = reinterpret_cast<const uint4*>(P.w1 + (size_t)(32 * mi + (lane & 3)) * 1376 + 176 * nj + 64 * cw + 8 * g);
#pragma unroll
      for (int s = 0; s < 8; s++) wv[s] = ok ? __ldg(wp + s * 688) : make_uint4(0, 0, 0, 0);
    }
#pragma unroll
    for (int c = 0; c < 2; c++) {
      const int ch = 4 * b + ((warp >> 1) & 2) + c, ix = ch * 128 + (tid & 127);
      prm[c][0] = __ldg((const unsigned short*)P.a_re + ix); prm[c][1] = __ldg((const unsigned short*)P.a_im + ix);
      prm[c][2] = __ldg((const unsigned short*)P.b_re + ix); prm[c][3] = __ldg((const unsigned short*)P.b_im + ix);
      prm[c][4] = __ldg((const unsigned short*)P.c_re + ix); prm[c][5] = __ldg((const unsigned short*)P.c_im + ix);
      prm[c][6] = __ldg((const unsigned short*)P.log_dt + ch); prm[c][7] = __ldg((const unsigned short*)P.dskip + ch);
    }
  } else if (warp < 2) {
    const bf16* pfp = warp == 0 ? P.w1 + (size_t)(2 * lane) * 1376 + 176 * nj : P.x + (size_t)(128 * mi + 4 * lane) * 512;
    asm volatile("prefetch.global.L2 [%0];" ::"l"(pfp));
  }
  if (warp > 4 && warp < 8) { __syncwarp(); nbar_arrive(2, 128); }
  if (warp == 4) nbar(2, 128); else nbar(0, 512);
  const int g = lane >> 2, q = lane & 3, mu = lane >> 3, r = lane & 7;

  if (__builtin_expect(warp < 8, 1)) {
    const int wg = warp >> 2;
    {
    const int w = warp & 3, t128 = tid & 127;
    const uint32_t stg0 = sb + SM_S0 + wg * 41984, stg1 = sb + SM_S0 + 21504 + wg * 40960;
    uint32_t xr[2][8];
    mbar_wait(BAR(B_LN), 0);
    if (tid == 0) TS1(36);
    {
      const uint32_t xa = sb + SM_LNX + (w >> 1) * 8192 + (128 * wg + (t128 & 63)) * 4;
#pragma unroll
      for (int i = 0; i < 8; i++) { xr[0][i] = lds32(xa + i * 1024); xr[1][i] = lds32(xa + i * 1024 + 256); }
    }
    {
      float v[16];
#pragma unroll
      for (int i = 0; i < 8; i++) {
        const float a = blo(xr[0][i]), d = bhi(xr[0][i]), e = blo(xr[1][i]), f = bhi(xr[1][i]);
        v[i] = (a + d) + (e + f);
        v[8 + i] = fmaf(a, a, d * d) + fmaf(e, e, f * f);
      }
      xred<8, 16>(v, lane);
      v[0] += __shfl_xor_sync(0xffffffffu, v[0], 1);
      const uint32_t red = sb + SM_RED + (w >> 1) * 256, wst = sb + SM_RED + 512 + warp * 64;
      if (!(lane & 1)) stsf(red + (lane >> 1) * 16 + (2 * wg + (w & 1)) * 4, v[0]);
      if (tid == 0) TS1(37);
      nbar(1, 256);
      if (tid == 0) TS1(38);
      const float4 p4 = lds128f(red + (lane & 15) * 16);
      const float tot = (p4.x + p4.y) + (p4.z + p4.w);
      const float oth = __shfl_xor_sync(0xffffffffu, tot, 8);
      if (lane < 8) {
        const float mean = tot * (1.f / 512.f);
        const float var = fmaxf(fmaf(-mean, mean, oth * (1.f / 512.f)), 0.f);
        const uint32_t mb = pk(mean, mean);
        const float den = bfr(sqrtf(bfr(bfr(var) + 1e-5f)));
        const float rs = __fdividef(1.f, den);
        sts64(wst + lane * 8, mb, __float_as_uint(rs));
        if (wg == 1 && !(w & 1)) {
          stsf(sb + SM_STST + (4 * w + lane) * 4, bhi(mb));
          stsf(sb + SM_STST + 64 + (4 * w + lane) * 4, rs);
        }
      }
      __syncwarp();
      uint32_t o[2][2][4];
#pragma unroll
      for (int i = 0; i < 8; i += 2) {
        const uint4 s2 = lds128(wst + i * 8);
        const float r0 = __uint_as_float(s2.y), r1 = __uint_as_float(s2.w);
#pragma unroll
        for (int c = 0; c < 2; c++) {
          const uint32_t d0 = hsub2(xr[c][i], s2.x), d1 = hsub2(xr[c][i + 1], s2.z);
          o[c][0][i >> 1] = pk(blo(d0) * r0, blo(d1) * r1);
          o[c][1][i >> 1] = pk(bhi(d0) * r0, bhi(d1) * r1);
        }
      }
      const bool sx = lane & 2;
#pragma unroll
      for (int c = 0; c < 2; c++) {
        const uint32_t da = (c ? stg1 : stg0) + (t128 & 63) * 64 + (w >> 1) * 16;
        const uint32_t *o0 = o[c][0], *o1 = o[c][1];
        sts128(da + (sx ? 32 : 0), sx ? o1[0] : o0[0], sx ? o1[1] : o0[1], sx ? o1[2] : o0[2], sx ? o1[3] : o0[3]);
        sts128(da + (sx ? 0 : 32), sx ? o0[0] : o1[0], sx ? o0[1] : o1[1], sx ? o0[2] : o1[2], sx ? o0[3] : o1[3]);
      }
      if (tid == 0) TS1(35);
      fence_async_smem();
      if (tid == 0) TS1(40);
      nbar(6 + wg, 128);
      if (w == 0) {
        if (elect_one()) {
          tma_st2(&tmXn, stg0, 256 * nj + 16 * mi, 256 * wg);
          tma_st2(&tmXn, stg1, 256 * nj + 16 * mi, 256 * wg + 128);
          if (wg == 1) bulk_st(g_stat + 32 * b, sb + SM_STST, 128);
          bulk_commit();
        }
        __syncwarp();
      }
      if (warp == 4 && elect_one()) {
        mbar_expect(BAR(B_F1 + 2), 16384);
        tma_ld2(sb + SM_LNX, &tmX, 128, 128 * mi, BAR(B_F1 + 2));
      }
      __syncwarp();
    if (warp > 4 && elect_one()) {
#pragma unroll
      for (int s = 2; s < 4; s++) {
        mbar_expect(BAR(B_F1 + s), 8192);
        tma_ld2(sb + ((0x5210 >> (4 * s)) & 15) * 24576 + (warp - 5) * 8192, &tmW1, 176 * nj + 64 * (warp - 5), 64 * s, BAR(B_F1 + s));
      }
    }
    __syncwarp();
      e0 = ld_rlx(&g_cnt[CNT_H(mi)]);
      if (tid == 0) TS1(39);
    }
    }
    {
      float acc[88];
      unsigned pv = 0;
#pragma unroll 1
      for (int ks = 0; ks < 8; ks++) {
        mbar_wait(BAR(B_F1 + ks), 0);
        if (ks == 0) TS(0 + wg);
        const uint32_t la = ((sb + 73728 + ((0x8618 >> (2 * ks)) & 3) * 16384 + wg * 8192) >> 4) | (1u << 16);
        const uint32_t lb = ((sb + ((0x5210 >> (4 * (ks & 3))) & 15) * 24576) >> 4) | (512u << 16);
        wg_fence();
#pragma unroll
        for (int k = 0; k < 4; k++) wg_ss176<HI_SW, HI_SW>(acc, la + 2 * k, lb + 128 * k, (ks | k) != 0);
        wg_commit();
        if (ks == 0) {
          if (!(warp & 3) && elect_one()) { bulk_wait0(); red_add(&g_cnt[CNT_P(wg)], 1); if (wg == 0) TS1(41); }
          __syncwarp();
        } else {
          wg_wait<1>();
          const int e = ks - 1;
          if (lane == 0) mbar_arrive(BAR(B_E1 + e));
          if (wg == 1) {
            if (e < (warp == 4 ? 5 : 6)) {
              mbar_wait(BAR(B_E1 + e), 0);
              if (elect_one()) {
                const int a = warp - 5;
                if (warp == 4) {
                  mbar_expect(BAR(B_F1 + e + 3), 16384);
                  tma_ld2(sb + 73728 + ((0x8618 >> (2 * e)) & 3) * 16384, &tmX, 64 * (e + 3), 128 * mi, BAR(B_F1 + e + 3));
                  if (e == 1) asm volatile("cp.async.bulk.prefetch.L2.global [%0], %1;" ::"l"((const char*)P.w2 + 11008 * b), "r"(11008) : "memory");
                } else if (e < 4) {
                  mbar_expect(BAR(B_F1 + e + 4), 8192);
                  tma_ld2(sb + ((0x5210 >> (4 * e)) & 15) * 24576 + a * 8192, &tmW1, 176 * nj + 64 * a, 64 * (e + 4), BAR(B_F1 + e + 4));
                } else {
                  const int i = 3 * (e - 4) + a;
                  mbar_expect(BAR(B_F2 + i), a < 2 ? 8192 : 6144);
                  tma_ld2(sb + i * 8192, a < 2 ? &tmW2 : &tmW2b, 64 * nj, 176 * (e == 4 ? nj : (nj == 0)) + 64 * a, BAR(B_F2 + i));
                }
              }
            }
          } else if (warp == 3 && ks >= 4 && ks < 6) {
            const unsigned* pp = &g_cnt[(lane & 1) ? CNT_CS(nj) : CNT_P(1)];
            if (ks == 4) pv = ld_rlx(pp);
            else {
              const unsigned ep = EPOCH;
#pragma unroll 1
              for (int i = 0; i < (1 << 22) && __any_sync(0xffffffffu, (int)(pv - ep) < 0); i++) pv = ld_rlx(pp);
              mbar_wait(BAR(B_E1 + 4), 0);
              if (elect_one()) {
                fence_async_glb();
                mbar_expect(BAR(B_MISC), 1024 + 704);
                bulk_ld(sb + SM_STAT, g_stat + 256 * mi, 1024, BAR(B_MISC));
                bulk_ld(sb + SM_COLS, g_colsum + (((ep >> 7) & 1) ^ 1) * 1408 + 176 * nj, 704, BAR(B_MISC));
                TS1(17);
              }
            }
          }
          __syncwarp();
        }
      }
      wg_wait<0>();
      if (lane == 0) mbar_arrive(BAR(B_E1 + 7));
      TS(2 + wg);
      mbar_wait(BAR(B_MISC), 0);
      mbar_wait(BAR(B_E1 + 6), 0);
      if (tid == 0) TS1(26);
      const uint32_t sa = sb + SM_STAT + (warp & 3) * 256 + (8 * wg + g) * 4;
      const float m0 = -ldsf(sa), m1 = -ldsf(sa + 128);
      const uint32_t ha = sb + SM_HR + (mu >> 1) * 128 + r * 16, rg = 2 * warp + (mu & 1);
#pragma unroll
      for (int i = 0; i < 22; i += 2) {
        uint32_t v[4];
#pragma unroll
        for (int u = 0; u < 2; u++) {
          const float2 cs = lds64f(sb + SM_COLS + (8 * (i + u) + 2 * q) * 4);
          const float* a = acc + 4 * (i + u);
          v[2 * u] = pk_relu(fmaf(m0, cs.x, a[0]), fmaf(m0, cs.y, a[1]));
          v[2 * u + 1] = pk_relu(fmaf(m1, cs.x, a[2]), fmaf(m1, cs.y, a[3]));
        }
        stsm4(ha + (i >> 3) * 16384 + (i & 7) * 128 + rg * (i < 16 ? 1024 : 768), v[0], v[1], v[2], v[3]);
      }
      fence_async_smem();
      __syncwarp();
      if (tid == 0) TS1(27);
      if (elect_one()) {
        unsigned char* hb = g_h + (size_t)b * 45056;
        bulk_st(hb + warp * 2048, sb + SM_HR + warp * 2048, 2048);
        bulk_st(hb + 16384 + warp * 2048, sb + SM_HR + 16384 + warp * 2048, 2048);
        bulk_st(hb + 32768 + warp * 1536, sb + SM_HR + 32768 + warp * 1536, 1536);
        bulk_commit();
        mbar_arrive(BAR(B_OWN));
      }
      __syncwarp();
    }
    if (wg == 1) {
      if (elect_one()) {
        bulk_wait0();
        red_add(&g_cnt[CNT_H(mi)], 2);
        if (warp == 4) {
          TS1(28);
          poll_cnt(&g_cnt[CNT_H(mi)], EPOCH);
          TS1(18);
          fence_async_glb();
          int s = 3, ph = 1, c = 0;
          const unsigned char* hs = g_h + (size_t)(8 * mi + (nj == 0)) * 45056;
          const unsigned char* own = g_h + (size_t)b * 45056;
#pragma unroll 1
          for (int i = 3; i < 24; i++) {
            mbar_wait(BAR(B_E2 + s), ph);
            const uint32_t nb = c < 2 ? 16384 : 12288;
            mbar_expect(BAR(B_F2 + s), nb);
            bulk_ld(sb + SM_HR + s * 16384, hs, nb, BAR(B_F2 + s));
            hs += nb;
            if (hs == own) hs += 45056;
            if (++c == 3) c = 0;
            if (++s == 6) { s = 0; ph ^= 1; }
          }
          mbar_wait(BAR(B_E2), ph);
          mbar_expect(BAR(B_X), 16384);
          tma_ld2(sb + SM_XT, &tmX, 64 * nj, 128 * mi, BAR(B_X));
        } else if (warp == 5) {
          int s = 0, ph = 0, c = 0, sl = 1 + (nj <= 1);
#pragma unroll 1
          for (int i = 6; i < 24; i++) {
            mbar_wait(BAR(B_E2 + s), ph);
            mbar_expect(BAR(B_F2 + s), c < 2 ? 8192 : 6144);
            tma_ld2(sb + s * 8192, c < 2 ? &tmW2 : &tmW2b, 64 * nj, 176 * sl + 64 * c, BAR(B_F2 + s));
            if (++c == 3) { c = 0; sl++; if (sl == nj) sl++; }
            if (++s == 6) { s = 0; ph ^= 1; }
          }
        }
      }
    } else {
      float acc[64];
      mbar_wait(BAR(B_OWN), 0);
      TS(6);
#pragma unroll 1
      for (int it = 0; it < 8; it++) {
        const int s0 = 3 * (it & 1), ph = (it >> 1) & 1;
#pragma unroll
        for (int c = 0; c < 3; c++) {
          const int s = s0 + c;
          mbar_wait(BAR(B_F2 + s), ph);
          const uint32_t la = ((sb + s * 8192) >> 4) | (512u << 16), lb = ((sb + SM_HR + s * 16384) >> 4) | (8u << 16);
          wg_fence();
          if (c < 2) {
#pragma unroll
            for (int k = 0; k < 4; k++) wg_ss128t<HI_SW, 64>(acc, la + 128 * k, lb + 16 * k, (it | c | k) != 0);
          } else {
#pragma unroll
            for (int k = 0; k < 3; k++) wg_ss128t<HI_SW, 48>(acc, la + 128 * k, lb + 16 * k, 1);
          }
          wg_commit();
          if (c == 2 && it == 0) {
            if (elect_one()) { bulk_wait0(); red_add(&g_cnt[CNT_H(mi)], 2); }
            __syncwarp();
          }
          wg_wait<1>();
          if (lane == 0 && (it | c) != 0) mbar_arrive(BAR(B_E2 + (c ? s - 1 : 5 - s0)));
          __syncwarp();
        }
        if (it == 0) TS(7);
      }
      wg_wait<0>();
      TS(8);
      mbar_wait(BAR(B_X), 0);
      const uint32_t xa = sb + SM_XT + (8 * (mu >> 1) + r) * 128 + (((2 * warp + (mu & 1)) ^ r) << 4);
      const uint32_t ya = sb + SM_YT + (16 * warp + 8 * (mu & 1) + r) * 128;
#pragma unroll
      for (int i = 0; i < 16; i += 2) {
        uint32_t xv[4];
        ldsm4t(xv, xa + i * 1024);
        const uint32_t ra = sb + SM_STAT + 64 + (i & 7) * 128 + (i >> 3) * 32 + q * 8;
        const float2 r0 = lds64f(ra), r1 = lds64f(ra + 128);
#pragma unroll
        for (int u = 0; u < 4; u++) {
          float* a = acc + 4 * (i + (u >> 1)) + 2 * (u & 1);
          const float2 rr = (u >> 1) ? r1 : r0;
          a[0] = fmaf(a[0], rr.x, blo(xv[u])); a[1] = fmaf(a[1], rr.y, bhi(xv[u]));
        }
      }
      mbar_wait(BAR(B_Y), 0);
      TS(9);
#pragma unroll
      for (int i = 0; i < 16; i += 2) {
        uint32_t yv[4], o[4];
        ldsm4(yv, ya + (i >> 3) * 8192 + ((((i & 7) + (mu >> 1)) ^ r) << 4));
#pragma unroll
        for (int u = 0; u < 4; u++) {
          const float* a = acc + 4 * (i + (u >> 1)) + 2 * (u & 1);
          o[u] = pk(a[0] + blo(yv[u]), a[1] + bhi(yv[u]));
        }
        stsm4t(xa + i * 1024, o[0], o[1], o[2], o[3]);
      }
      fence_async_smem();
      nbar(8, 128);
      if (warp == 0 && elect_one()) {
        tma_st2(&tmOut, sb + SM_XT, 64 * nj, 128 * mi);
        bulk_commit();
        bulk_wait0_read();
      }
      TS(10);
    }
  } else {
#define UK2 3
#define SPW 2
#define DNW 1
#define DNB 3
    const int wg = (warp >> 2) & 1, w = warp & 3, t128 = tid & 127, ch = 4 * b + 2 * wg, nb = 4 + wg;
    const uint32_t ub = sb + SM_S0 + wg * 2 * BLK, kt = ub + O_KT, wk = ub + O_WK;
    const uint32_t stg0 = sb + SM_S0 + wg * 41984, stg1 = sb + SM_S0 + 21504 + wg * 40960;
    {
#pragma unroll
      for (int c = 0; c < 2; c++) {
        float pf[7];
#pragma unroll
        for (int i = 0; i < 7; i++) pf[i] = __uint_as_float((uint32_t)prm[c][i] << 16);
        const float dt = bfr(expf(pf[6]));
        const float ar = dt * pf[0], ai = dt * pf[1];
        const float arl = ar * 1.4426950408889634f;
        float2 wv = cmul(make_float2(pf[4], pf[5]), make_float2(dt * pf[2], dt * pf[3]));
        const float2 z1 = cexp_p(arl, ai, 1.f), z32 = cexp_p(arl, ai, 32.f), z256 = cexp_p(arl, ai, 256.f);
        sts128f(kt + c * BLK + 256 + ((t128 * 16) ^ (t128 & 64)), 8.f * arl, red2pi(8.f * ai), z32.x, z32.y);
        const uint32_t bt = ub + c * BLK + O_BT + ((t128 & 63) >> 2) * 752 + (t128 & 3) * 4 + (t128 >> 6) * 384;
        float2 v0, v4;
#pragma unroll
        for (int i = 0; i <= 8; i++) {
          if (i < 8) sts32(bt + i * 16, pk(wv.x, -wv.y));
          if (!(i & 1)) {
            const float2 t = cmul(wv, z256);
            sts32(bt + (i < 8 ? 8 + (i >> 1) : 18) * 16, pk(t.x, -t.y));
            if (i == 0) v0 = t;
            if (i == 4) v4 = t;
          }
          if (i < 8) wv = cmul(wv, z1);
        }
        v0 = cmul(v0, z256); v4 = cmul(v4, z256);
        sts32(bt + 12 * 16, pk(v0.x, -v0.y)); sts32(bt + 13 * 16, pk(v4.x, -v4.y));
        v0 = cmul(v0, z256); v4 = cmul(v4, z256);
        sts32(bt + 14 * 16, pk(v0.x, -v0.y)); sts32(bt + 15 * 16, pk(v4.x, -v4.y));
        v0 = cmul(v0, z256); sts32(bt + 16 * 16, pk(v0.x, -v0.y));
        v0 = cmul(v0, z256); sts32(bt + 17 * 16, pk(v0.x, -v0.y));
        v0 = cmul(v0, z256); sts32(bt + 20 * 16, pk(v0.x, -v0.y));
        v0 = cmul(v0, z256); sts32(bt + 21 * 16, pk(v0.x, -v0.y));
        v0 = cmul(v0, z256); sts32(bt + 19 * 16, pk(v0.x, -v0.y));
      }
      fence_async_smem();
      if (tid == 256) TS1(42);
      nbar(nb, 128);
      if (warp > 12) {
        const int cw = warp - 13;
        float* cs = g_colsum + 176 * nj + 64 * cw;
        const uint32_t par = (e0 >> 7) & 1;
        if (mi == 0 && (cw < 2 || lane < 24)) *reinterpret_cast<float2*>(cs + (par ^ 1) * 1408 + 2 * lane) = make_float2(0.f, 0.f);
        const uint32_t sel = g == 0 ? 0x00003F80u : g == 1 ? 0x3F800000u : 0u;
        float d0[4] = {0.f, 0.f, 0.f, 0.f}, d1[4] = {0.f, 0.f, 0.f, 0.f};
#pragma unroll
        for (int s = 0; s < 8; s += 2) {
          mma16816(d0, wv[s].x, wv[s].y, wv[s + 1].x, wv[s + 1].y, sel);
          mma16816(d1, wv[s].z, wv[s].w, wv[s + 1].z, wv[s + 1].w, sel);
        }
        const uint32_t st = sb + SM_CSST + cw * 256;
        if (q == 0) { sts128f(st + g * 32, d0[0], d0[1], d0[2], d0[3]); sts128f(st + g * 32 + 16, d1[0], d1[1], d1[2], d1[3]); }
        fence_async_smem();
        __syncwarp();
        if (elect_one()) { bulk_red_f32(cs + par * 1408, st, cw < 2 ? 256 : 192); bulk_commit(); }
        __syncwarp();
      }
      if (tid == 256) TS1(43);
      float ka[2][24];
      unsigned pv;
      const float jf = (float)(8 * w + (g & 3));
      const uint32_t pp = kt + 256 + (g >> 2) * 1024 + q * 16, lbt = ((ub + O_BT) >> 4) | (47u << 16);
#pragma unroll
      for (int k2 = 0; k2 < 4; k2++) {
        uint32_t af[4][4];
        if (k2 == UK2) pv = ld_rlx(&g_cnt[CNT_P(lane & 1)]);
        if (k2 >= 2) wg_wait<1>();
#pragma unroll
        for (int k = 0; k < 4; k++) {
#pragma unroll
          for (int hh = 0; hh < 2; hh++) {
            const float4 p = lds128f(pp + (k & 1) * BLK + (2 * k2 + (k >> 1)) * 128 + ((hh * 64) ^ ((lane & 16) << 2)));
            const float m = ex2(p.x * jf), ph = p.y * jf;
            const float2 e = make_float2(m * __cosf(ph), m * __sinf(ph));
            const float2 e4 = cmul(e, make_float2(p.z, p.w));
            af[k][2 * hh] = pk(e.x, e.y);
            af[k][2 * hh + 1] = pk(e4.x, e4.y);
          }
        }
        wg_fence();
#pragma unroll
        for (int k = 0; k < 4; k++) {
          if (k2 == 0 && k < 2) wg_rs48<0>(ka[k & 1], af[k][0], af[k][1], af[k][2], af[k][3], lbt + (k & 1) * (BLK / 16));
          else wg_rs48<1>(ka[k & 1], af[k][0], af[k][1], af[k][2], af[k][3], lbt + (k & 1) * (BLK / 16) + (2 * k2 + (k >> 1)) * 94);
        }
        wg_commit();
        if (k2 == 1 && warp > 12) {
          if (elect_one()) { bulk_wait0(); red_add(&g_cnt[CNT_CS(nj)], warp < 15 ? 3 : 2); }
          __syncwarp();
        }
        if (k2 == UK2) {
#pragma unroll 1
          for (int i = 0; i < (1 << 22) && __any_sync(0xffffffffu, (int)(pv - EPOCH) < 0); i++) pv = ld_rlx(&g_cnt[CNT_P(lane & 1)]);
          if (tid == 256) TS1(16);
          sts128(ub + (w >> 1) * BLK + (4 * (w & 1) + mu) * U_PL + r * 16, 0, 0, 0, 0);
          if (elect_one()) {
            fence_async_glb();
            mbar_expect(BAR(B_U + wg), 2048);
#pragma unroll
            for (int i = 0; i < 4; i++)
              bulk_ld(ub + (w >> 1) * BLK + (4 * (w & 1) + i) * U_PL + 128, g_xnP + (size_t)(ch * 8 + 4 * w + i) * 256, 512, BAR(B_U + wg));
          }
          __syncwarp();
        }
      }
      if (tid == 256) TS1(44);
      wg_wait<0>();
      float kv[2][6];
#pragma unroll
      for (int i = 0; i < 12; i++) {
        const int c = i / 6, x = 4 * ((i % 6) >> 1) + (i & 1);
        const float snd = (lane & 16) ? ka[c][12 + x] : ka[c][x + 2], kp = (lane & 16) ? ka[c][14 + x] : ka[c][x];
        kv[c][i % 6] = kp + __shfl_xor_sync(0xffffffffu, snd, 16);
      }
      nbar(nb, 128);
      if (tid == 256) TS1(45);
      if (t128 < 109) {
        const int z = t128 - 16, zi = z >= 62 ? 2 : z >= 31 ? 1 : 0;
        const uint32_t za = kt + (z < 0 ? t128 * 16 : 2304 + zi * (640 - 496) + z * 16);
        sts128(za, 0, 0, 0, 0); sts128(za + BLK, 0, 0, 0, 0);
      }
      if (lane < (w ? 7 : 22)) {
        const uint32_t za = wk + (w == 0 ? WK_S5 : w == 1 ? WK_S3 : w == 2 ? WK_S9 : WK_S7) + lane * 16;
        sts128(za, 0, 0, 0, 0); sts128(za + BLK, 0, 0, 0, 0);
      }
      const int j = 8 * w + g;
#pragma unroll
      for (int c = 0; c < 2; c++) {
        const uint32_t kc = kt + c * BLK;
        float a = kv[c][0], d = kv[c][1];
        const uint32_t p0 = kc + 256 + (8 * j + 2 * q) * 4;
        if (j == 0 && q == 0) { a += __uint_as_float((uint32_t)prm[c][7] << 16); sts16(p0 + 2, 0); }
        uint32_t ca = pk(d, a);
        sts16(p0, ca >> 16);
        sts32(p0 + 4, ca);
        sts16(p0 + 10, ca & 0xffff);
        a = kv[c][2]; d = kv[c][3];
        if (j == 31 && q == 1) d -= kv[c][4];
        ca = pk(d, a);
        if (q < 2) {
          const uint32_t p1 = kc + 256 + (256 + 8 * j + 4 * q) * 4, aa = __byte_perm(ca, 0, 0x3232);
          if (j | q) { sts16(p1 - 4, aa); sts64(p1, aa, aa); }
          else { sts16(p1, aa); sts32(p1 + 4, aa); }
          sts32(p1 + 8, ca);
          sts16(p1 + 14, ca & 0xffff);
          if (j == 31 && q == 1) sts16(p1 + 12, 0);
        } else {
          sts16(kc + KT_Z5 + (32 * q + j) * 2, ca >> 16);
          sts16(kc + KT_Z3 + (32 * q + j) * 2, ca & 0xffff);
        }
        ca = pk(kv[c][5], kv[c][4]);
        if (!(q & 1)) {
          if (j | q) sts16(kc + KT_Z4 + (55 + 32 * q + j) * 2, ca >> 16);
          else { sts128(kc + KT_Z5 + 256, ca >> 16, 0, 0, 0); sts128(kc + KT_Z3 + 256, ca >> 16, 0, 0, 0); }
          sts16(kc + KT_Z4 + (87 + 32 * q + j) * 2, ca & 0xffff);
        } else if (q == 1 && j == 0) {
          sts16(kc + KT_Z4 + 183 * 2, ca & 0xffff);
        }
      }
      if (tid == 256) TS1(46);
    }
    mbar_wait(BAR(B_U + wg), 0);
    if (tid == 256) TS1(25);
#pragma unroll
    for (int it = 0; it < 3; it++) {
      const int ci = it < 2 ? t128 : 128 + (t128 & 63);
      const uint32_t co = it < 2 ? it * BLK : (t128 >> 6) * BLK;
      float u[24];
#pragma unroll
      for (int k = 0; k < 3; k++) {
        const int cc = ci - 1 + k;
        const uint4 vv = lds128(ub + co + (cc & 7) * U_PL + ((cc >> 3) + 8) * 16);
        u[8 * k + 0] = blo(vv.x); u[8 * k + 1] = bhi(vv.x); u[8 * k + 2] = blo(vv.y); u[8 * k + 3] = bhi(vv.y);
        u[8 * k + 4] = blo(vv.z); u[8 * k + 5] = bhi(vv.z); u[8 * k + 6] = blo(vv.w); u[8 * k + 7] = bhi(vv.w);
      }
      float f2[18], s5[10], t8[8];
      const uint32_t wa = wk + co + ci * 16;
#pragma unroll
      for (int i = 4; i < 18; i++) f2[i] = u[i] + u[i + 1];
#pragma unroll
      for (int i = 0; i < 10; i++) s5[i] = (f2[i + 6] + f2[i + 8]) + u[i + 10];
      sts128(wa + WK_S5 + 23 * 16, pk(s5[0], s5[1]), pk(s5[2], s5[3]), pk(s5[4], s5[5]), pk(s5[6], s5[7]));
#pragma unroll
      for (int i = 0; i < 8; i++) t8[i] = f2[i + 4] + u[i + 3];
      sts128(wa + WK_S3 + 7 * 16, pk(t8[0], t8[1]), pk(t8[2], t8[3]), pk(t8[4], t8[5]), pk(t8[6], t8[7]));
      if (it < 2) {
        if (t128 == 0) {
          const uint32_t p12 = pk(u[8], f2[8]), p34 = pk(t8[5], f2[8] + f2[10]);
          sts128(wa + WK_S5 + 22 * 16, 0, 0, 0, p12);
          sts128(wa + WK_S7 + 7 * 16, 0, 0, p12 << 16, __byte_perm(p12, p34, 0x5432));
          sts128(wa + WK_S9 + 7 * 16, 0, 0, p12, p34);
        }
#pragma unroll
        for (int i = 0; i < 8; i++) t8[i] = f2[i + 5] + s5[i + 1];
        sts128(wa + WK_S7 + 8 * 16, pk(t8[0], t8[1]), pk(t8[2], t8[3]), pk(t8[4], t8[5]), pk(t8[6], t8[7]));
#pragma unroll
        for (int i = 0; i < 8; i++) t8[i] = (f2[i + 4] + f2[i + 6]) + s5[i + 2];
        sts128(wa + WK_S9 + 8 * 16, pk(t8[0], t8[1]), pk(t8[2], t8[3]), pk(t8[4], t8[5]), pk(t8[6], t8[7]));
      }
    }
    if (tid == 256) TS1(54);
    fence_async_smem();
    nbar(nb, 128);
    mbar_wait(BAR(B_E1 + GATE), 0);
    if (tid == 256) TS1(55);
    float dacc[2][16];
    {
      const uint32_t pa = kt + (16 * w + g - 2 * q + 520 + 64) * 4, lu = (ub >> 4) | ((U_PL >> 4) << 16);
      uint32_t hprev[2] = {lds32(pa), lds32(pa + BLK)};
#pragma unroll
      for (int blk = 0; blk < 36 / DNB; blk++) {
        uint32_t h[2][2 * DNB + 1];
        if (blk > DNW) wg_wait<DNW>();
#pragma unroll
        for (int c = 0; c < 2; c++) {
          h[c][0] = hprev[c];
#pragma unroll
          for (int i = 1; i <= 2 * DNB; i++) h[c][i] = lds32(pa + c * BLK - (2 * DNB * blk + i) * 32);
          hprev[c] = h[c][2 * DNB];
        }
        wg_fence();
#pragma unroll
        for (int k = 0; k < 2 * DNB; k++) {
          const int c = k & 1, x = k >> 1, kap = DNB * blk + x;
          if (kap == 0) wg_rs32<0>(dacc[c], h[c][1], h[c][0], h[c][2], h[c][1], lu + c * (BLK / 16));
          else wg_rs32<1>(dacc[c], h[c][2 * x + 1], h[c][2 * x], h[c][2 * x + 2], h[c][2 * x + 1], lu + c * (BLK / 16) + (kap & 3) * (U_PL >> 3) + (kap >> 2));
        }
        wg_commit();
      }
    }
    if (tid == 256) TS1(56);
    {
      const int kk = r + 8 * (mu >> 1), cofs = 15 - kk + 2 * w + (mu & 1);
      const uint32_t a5 = wk + cofs * 16, a4 = a5 + ((kk & 1) ? WK_S9 : WK_S7), lz = (kt >> 4) | (1u << 16);
#pragma unroll
      for (int blk = 0; blk < 17; blk++) {
        uint32_t f[4][4];
        wg_wait<SPW>();
#pragma unroll
        for (int k = 0; k < (blk < 16 ? 4 : 2); k++) {
          const int x = 2 * blk + (k >> 1);
          ldsm4t(f[k], (k & 1) * BLK + (x < 13 ? a5 + WK_S5 + x * 256 : x < 25 ? a5 + WK_S3 + (x - 13) * 256 : a4 + (x - 25) * 256));
        }
        wg_fence();
#pragma unroll
        for (int k = 0; k < (blk < 16 ? 4 : 2); k++) {
          const int x = 2 * blk + (k >> 1);
          const int zo = x < 13 ? KT_Z5 + 16 - 32 * x : x < 25 ? KT_Z3 - 16 - 32 * (x - 13) : KT_Z4 - 160 - 32 * (x - 25);
          wg_rs32<1>(dacc[k & 1], f[k][0], f[k][1], f[k][2], f[k][3], lz + ((k & 1) * BLK + zo) / 16);
        }
        wg_commit();
      }
      uint32_t fx[2][8];
      float kf[2];
#pragma unroll
      for (int c = 0; c < 2; c++) {
#pragma unroll
        for (int hh = 0; hh < 2; hh++) {
          const int m5 = 16 * w + g + 8 * hh + 59;
          const uint32_t fa = ub + c * BLK + ((m5 >> 3) & 7) * U_PL + (7 + (m5 >> 6) + 2 * q) * 16 + (m5 & 7) * 2;
          fx[c][4 * hh] = lds16(fa); fx[c][4 * hh + 1] = lds16(fa + 16); fx[c][4 * hh + 2] = lds16(fa + 128); fx[c][4 * hh + 3] = lds16(fa + 144);
        }
        kf[c] = -blo(lds32(kt + c * BLK + KT_Z5 + 256));
      }
      wg_wait<0>();
      if (tid == 256) TS1(57);
      nbar(nb, 128);
#pragma unroll
      for (int c = 0; c < 2; c++) {
        float* d = dacc[c];
#pragma unroll
        for (int i = 0; i < 8; i++) {
          const int x = 8 + 4 * ((i >> 1) & 1) + 2 * (i >> 2) + (i & 1);
          d[x] = fmaf(kf[c], blo(fx[c][i]), d[x]);
        }
#pragma unroll
        for (int i = 0; i < 4; i += 2) {
          const int n = 8 * (i + (mu >> 1)) + r;
          stsm4t((c ? stg1 : stg0) + n * 128 + (((2 * w + (mu & 1)) ^ r) << 4), pk(d[4 * i], d[4 * i + 1]), pk(d[4 * i + 2], d[4 * i + 3]),
                 pk(d[4 * i + 4], d[4 * i + 5]), pk(d[4 * i + 6], d[4 * i + 7]));
        }
      }
      fence_async_smem();
      nbar(nb, 128);
      if (w == 0 && elect_one()) {
        tma_st2(&tmYst, stg0, 0, ch * 32);
        tma_st2(&tmYst, stg1, 0, ch * 32 + 32);
        bulk_commit();
        bulk_wait0();
        red_add(&g_cnt[CNT_Y(b >> 4)], 4);
        if (wg == 0) {
          TS1(23);
        } else {
          poll_cnt(&g_cnt[CNT_Y(nj)], EPOCH);
          fence_async_glb();
          mbar_expect(BAR(B_Y), 16384);
          tma_ld2(sb + SM_YT, &tmYld, 128 * mi, 64 * nj, BAR(B_Y));
          tma_ld2(sb + SM_YT + 8192, &tmYld, 128 * mi + 64, 64 * nj, BAR(B_Y));
          TS1(20);
        }
      }
    }
  }
}

typedef CUresult (*PFN_enc)(CUtensorMap*, CUtensorMapDataType, cuuint32_t, void*, const cuuint64_t*, const cuuint64_t*, const cuuint32_t*,
                            const cuuint32_t*, CUtensorMapInterleave, CUtensorMapSwizzle, CUtensorMapL2promotion, CUtensorMapFloatOOBfill);

static void make_map(PFN_enc enc, CUtensorMap* m, const void* ptr, uint64_t cols, uint64_t rows, uint32_t bc, uint32_t br, bool sw) {
  cuuint64_t dims[2] = {cols, rows};
  cuuint64_t strides[1] = {cols * 2};
  cuuint32_t box[2] = {bc, br};
  cuuint32_t es[2] = {1, 1};
  enc(m, CU_TENSOR_MAP_DATA_TYPE_BFLOAT16, 2, const_cast<void*>(ptr), dims, strides, box, es, CU_TENSOR_MAP_INTERLEAVE_NONE,
      sw ? CU_TENSOR_MAP_SWIZZLE_128B : CU_TENSOR_MAP_SWIZZLE_NONE, CU_TENSOR_MAP_L2_PROMOTION_L2_128B, CU_TENSOR_MAP_FLOAT_OOB_FILL_NONE);
}

extern "C" void kernel_launch(void* const* d_in, const int* in_sizes, int n_in, void* d_out, int out_size) {
  (void)in_sizes; (void)n_in; (void)out_size;
  static PFN_enc enc = nullptr;
  static void *py = nullptr, *px = nullptr;
  if (!enc) {
    void* fn = nullptr;
    cudaDriverEntryPointQueryResult qr;
    cudaGetDriverEntryPoint("cuTensorMapEncodeTiled", &fn, cudaEnableDefault, &qr);
    enc = (PFN_enc)fn;
    cudaGetSymbolAddress(&py, g_yT);
    cudaGetSymbolAddress(&px, g_xnP);
    cudaFuncSetAttribute(fused_kernel, cudaFuncAttributeMaxDynamicSharedMemorySize, SM_TOTAL);
  }
  CUtensorMap tmX, tmW1, tmW2, tmW2b, tmYst, tmYld, tmOut, tmXn;
  make_map(enc, &tmX, d_in[0], 512, 2048, 64, 128, true);
  make_map(enc, &tmW1, d_in[10], 1376, 512, 64, 64, true);
  make_map(enc, &tmW2, d_in[11], 512, 1376, 64, 64, true);
  make_map(enc, &tmW2b, d_in[11], 512, 1376, 64, 48, true);
  make_map(enc, &tmYst, py, 64, 512 * 32, 64, 32, true);
  make_map(enc, &tmYld, py, 2048, 512, 64, 64, true);
  make_map(enc, &tmOut, d_out, 512, 2048, 64, 128, true);
  make_map(enc, &tmXn, px, 2048, 512, 16, 128, false);
  Params P;
  P.x = (const bf16*)d_in[0]; P.a_re = (const bf16*)d_in[1]; P.a_im = (const bf16*)d_in[2];
  P.b_re = (const bf16*)d_in[3]; P.b_im = (const bf16*)d_in[4]; P.c_re = (const bf16*)d_in[5]; P.c_im = (const bf16*)d_in[6];
  P.log_dt = (const bf16*)d_in[7]; P.dskip = (const bf16*)d_in[8]; P.w1 = (const bf16*)d_in[10]; P.w2 = (const bf16*)d_in[11];
  fused_kernel<<<128, 512, SM_TOTAL, cudaStreamPerThread>>>(P, tmX, tmW1, tmW2, tmW2b, tmYst, tmYld, tmOut, tmXn);
}
```
